```python
import torch

def _softmax(x, axis=-1):
    return torch.softmax(x, dim=axis)
def _gelu(x):
    return torch.nn.functional.gelu(x, approximate="tanh")
def _silu(x):
    return torch.nn.functional.silu(x)
def _sigmoid(x):
    return torch.sigmoid(x)
def _layernorm(x, axis=-1, eps=1e-5):
    m = x.mean(dim=axis, keepdim=True)
    v = x.var(dim=axis, keepdim=True, unbiased=False)
    return (x - m) / torch.sqrt(v + eps)
def _scatter_add(tgt, idx, src, axis=0):
    return tgt.clone().index_add_(axis, idx, src)
def _segment_sum(src, seg, n):
    out = torch.zeros((n,) + src.shape[1:], dtype=src.dtype)
    return out.index_add_(0, seg, src)
def _pad(x, pw):
    flat = tuple(v for pair in reversed(pw) for v in pair)
    return torch.nn.functional.pad(x, flat)

kernel_name = 'recurrent_scan__spectral_gfnet__swiglu_ffn__prompt'

def setup_inputs():

    _w = (lambda a: (lambda t: t.to(torch.bfloat16) if t.is_floating_point() else t)(torch.as_tensor(a)))
    def _A_setup():
        B, S, D = 1, 2048, 448
        Df = D // 2 + 1
        return {
            "x": _w((lambda *s: torch.randn(*s, dtype=torch.bfloat16) * 0.05)(B, S, D)),
            "w_r": _w((lambda *s: torch.randn(*s, dtype=torch.bfloat16) * 0.2)(S, Df) * 0.02),
            "w_i": _w((lambda *s: torch.randn(*s, dtype=torch.bfloat16) * 0.2)(S, Df) * 0.02),
        }
    _A_in = _A_setup()

    def _B_setup():
        B, S, D, F = 1, 2048, 448, 1792
        return {
            "x": _w((lambda *s: torch.randn(*s, dtype=torch.bfloat16) * 0.05)(B, S, D)),
            "w_gate": _w((lambda *s: torch.randn(*s, dtype=torch.bfloat16) * 0.2)(D, F)),
            "w_up": _w((lambda *s: torch.randn(*s, dtype=torch.bfloat16) * 0.2)(D, F)),
            "w_down": _w((lambda *s: torch.randn(*s, dtype=torch.bfloat16) * 0.2)(F, D)),
        }
    _B_in = _B_setup()

    return {
        "A_x": _A_in["x"],
        "A_w_r": _A_in["w_r"],
        "A_w_i": _A_in["w_i"],
        "B_x": _B_in["x"],
        "B_w_gate": _B_in["w_gate"],
        "B_w_up": _B_in["w_up"],
        "B_w_down": _B_in["w_down"],
    }

def reference(A_x, A_w_r, A_w_i, B_x, B_w_gate, B_w_up, B_w_down):
    def _A_ref(x, w_r, w_i):
        B, S, D = x.shape
        X = (lambda x, axes=(-2,-1): torch.fft.rfft2(x.float(), dim=axes))(x, axes=(-2, -1))
        W = w_r + 1j * w_i
        X = X * W
        y = (lambda x, s, axes=(-2,-1): torch.fft.irfft2(x, s=s, dim=axes).to(torch.bfloat16))(X, (S, D), axes=(-2, -1))
        return y

    def _B_ref(x, w_gate, w_up, w_down):
        g = _silu(x @ w_gate)
        u = x @ w_up
        return (g * u) @ w_down

    x = A_x
    xn = _layernorm(x, axis=-1)
    s = _A_ref(xn, A_w_r, A_w_i)
    g = _silu(_B_ref(xn, B_w_gate, B_w_up, B_w_down))
    return x + s * g
```

```cpp
#include <cuda_runtime.h>
#include <cuda_bf16.h>
#include <cuda.h>
#include <stdint.h>

namespace {

constexpr int kS = 2048, kD = 448, kF = 1792, kCols = 225;

constexpr uint32_t SM_X = 0;
constexpr uint32_t SM_RING = 114688;
constexpr uint32_t SM_T16 = SM_RING + 5 * 16384;
constexpr uint32_t SM_FD = SM_T16 + 16384;
constexpr uint32_t SM_STATS = SM_FD + 16384;
constexpr uint32_t SM_CS = SM_STATS + 1024;
constexpr uint32_t SM_BAR = SM_CS + 1792;
constexpr uint32_t SM_TOTAL = SM_BAR + 256;
constexpr uint32_t BAR_FULL = SM_BAR, BAR_EMPTY = SM_BAR + 40, BAR_X = SM_BAR + 80, BAR_T = SM_BAR + 136,
                   BAR_S = SM_BAR + 144, BAR_R = SM_BAR + 152, BAR_C = SM_BAR + 160, BAR_CD = SM_BAR + 168,
                   BAR_WT = SM_BAR + 176, BAR_XF = SM_BAR + 184, BAR_E = SM_BAR + 192, BAR_S1 = SM_BAR + 200,
                   SM_EPOCH = SM_BAR + 216;
constexpr int kNumBars = 27;
constexpr int kStages = 5;
constexpr int kNumLoads = 42;
#define LAG 2
constexpr int kLag = LAG;
#define DRY0 0
constexpr uint32_t CNT_A = 64, CNT_Z = 96, CNT_P = 128;

__device__ __align__(1024) uint16_t g_At[kCols * 2 * kS];
__device__ __align__(1024) uint32_t g_Wt[kCols * kS];
__device__ __align__(1024) uint16_t g_Zt[kCols * 2 * kS];
__device__ __align__(1024) uint4 g_P[128 * 8 * 896];
__device__ __align__(1024) uint2 g_stats[kS];
__device__ __align__(1024) uint2 g_csum[4 * kF];
__device__ __align__(1024) uint32_t g_cnt[128 + 1024];
#define TL(idx) do {} while (0)
#define TL2(k, idx) do {} while (0)
#define TLG(idx) do {} while (0)
#define TLS(k, idx) do {} while (0)
__device__ __align__(1024) const uint32_t g_T16[4096] = {
  0x3f803f80u,0x3f803f80u,0x3f803f80u,0x3f803f80u,0x3f803f80u,0x3f803f80u,0x3f803f80u,0x3f803f80u,
  0x3f803f80u,0x3f803f80u,0x3f803f80u,0x3f803f80u,0x3f803f80u,0x3f803f80u,0x3f803f80u,0x3f803f80u,
  0x3f803f80u,0x3f803f80u,0x3f803f80u,0x3f803f80u,0x3f803f80u,0x3f803f80u,0x3f803f80u,0x3f803f80u,
  0x3f803f80u,0x3f803f80u,0x3f803f80u,0x3f803f80u,0x3f803f80u,0x3f803f80u,0x3f803f80u,0x3f803f80u,
  0x3f553f6du,0x3e483ec4u,0xbf0ebec4u,0xbf7bbf6du,0x3f7b3f80u,0x3f0e3f35u,0xbe480000u,0xbf55bf35u,
  0xbf55bf6du,0xbe48bec4u,0x3f0e3ec4u,0x3f7b3f6du,0xbf7bbf80u,0xbf0ebf35u,0x3e480000u,0x3f553f35u,
  0x3f553f6du,0x3e483ec4u,0xbf0ebec4u,0xbf7bbf6du,0x3f7b3f80u,0x3f0e3f35u,0xbe480000u,0xbf55bf35u,
  0xbf55bf6du,0xbe48bec4u,0x3f0e3ec4u,0x3f7b3f6du,0xbf7bbf80u,0xbf0ebf35u,0x3e480000u,0x3f553f35u,
  0x3f6d3f80u,0xbec40000u,0xbf6dbf80u,0x3ec40000u,0x3ec43f35u,0xbf6dbf35u,0xbec4bf35u,0x3f6d3f35u,
  0x3f6d3f80u,0xbec40000u,0xbf6dbf80u,0x3ec40000u,0x3ec43f35u,0xbf6dbf35u,0xbec4bf35u,0x3f6d3f35u,
  0x3f6d3f80u,0xbec40000u,0xbf6dbf80u,0x3ec40000u,0x3ec43f35u,0xbf6dbf35u,0xbec4bf35u,0x3f6d3f35u,
  0x3f6d3f80u,0xbec40000u,0xbf6dbf80u,0x3ec40000u,0x3ec43f35u,0xbf6dbf35u,0xbec4bf35u,0x3f6d3f35u,
  0x3e48bec4u,0x3f0e3f6du,0xbf7bbf6du,0x3f553ec4u,0xbf55bf80u,0x3f7b3f35u,0xbf0e0000u,0xbe48bf35u,
  0xbe483ec4u,0xbf0ebf6du,0x3f7b3f6du,0xbf55bec4u,0x3f553f80u,0xbf7bbf35u,0x3f0e0000u,0x3e483f35u,
  0x3e48bec4u,0x3f0e3f6du,0xbf7bbf6du,0x3f553ec4u,0xbf55bf80u,0x3f7b3f35u,0xbf0e0000u,0xbe48bf35u,
  0xbe483ec4u,0xbf0ebf6du,0x3f7b3f6du,0xbf55bec4u,0x3f553f80u,0xbf7bbf35u,0x3f0e0000u,0x3e483f35u,
  0x3f353f80u,0xbf35bf80u,0x3f353f80u,0xbf35bf80u,0xbf350000u,0x3f350000u,0xbf350000u,0x3f350000u,
  0x3f353f80u,0xbf35bf80u,0x3f353f80u,0xbf35bf80u,0xbf350000u,0x3f350000u,0xbf350000u,0x3f350000u,
  0x3f353f80u,0xbf35bf80u,0x3f353f80u,0xbf35bf80u,0xbf350000u,0x3f350000u,0xbf350000u,0x3f350000u,
  0x3f353f80u,0xbf35bf80u,0x3f353f80u,0xbf35bf80u,0xbf350000u,0x3f350000u,0xbf350000u,0x3f350000u,
  0xbf7bbec4u,0x3f553f6du,0xbe48bf6du,0xbf0e3ec4u,0x3f0e3f80u,0x3e48bf35u,0xbf550000u,0x3f7b3f35u,
  0x3f7b3ec4u,0xbf55bf6du,0x3e483f6du,0x3f0ebec4u,0xbf0ebf80u,0xbe483f35u,0x3f550000u,0xbf7bbf35u,
  0xbf7bbec4u,0x3f553f6du,0xbe48bf6du,0xbf0e3ec4u,0x3f0e3f80u,0x3e48bf35u,0xbf550000u,0x3f7b3f35u,
  0x3f7b3ec4u,0xbf55bf6du,0x3e483f6du,0x3f0ebec4u,0xbf0ebf80u,0xbe483f35u,0x3f550000u,0xbf7bbf35u,
  0x3ec43f80u,0x3f6d0000u,0xbec4bf80u,0xbf6d0000u,0xbf6dbf35u,0xbec43f35u,0x3f6d3f35u,0x3ec4bf35u,
  0x3ec43f80u,0x3f6d0000u,0xbec4bf80u,0xbf6d0000u,0xbf6dbf35u,0xbec43f35u,0x3f6d3f35u,0x3ec4bf35u,
  0x3ec43f80u,0x3f6d0000u,0xbec4bf80u,0xbf6d0000u,0xbf6dbf35u,0xbec43f35u,0x3f6d3f35u,0x3ec4bf35u,
  0x3ec43f80u,0x3f6d0000u,0xbec4bf80u,0xbf6d0000u,0xbf6dbf35u,0xbec43f35u,0x3f6d3f35u,0x3ec4bf35u,
  0x3f0e3f6du,0x3f7b3ec4u,0x3f55bec4u,0x3e48bf6du,0xbe48bf80u,0xbf55bf35u,0xbf7b0000u,0xbf0e3f35u,
  0xbf0ebf6du,0xbf7bbec4u,0xbf553ec4u,0xbe483f6du,0x3e483f80u,0x3f553f35u,0x3f7b0000u,0x3f0ebf35u,
  0x3f0e3f6du,0x3f7b3ec4u,0x3f55bec4u,0x3e48bf6du,0xbe48bf80u,0xbf55bf35u,0xbf7b0000u,0xbf0e3f35u,
  0xbf0ebf6du,0xbf7bbec4u,0xbf553ec4u,0xbe483f6du,0x3e483f80u,0x3f553f35u,0x3f7b0000u,0x3f0ebf35u,
  0x00000000u,0x00000000u,0x00000000u,0x00000000u,0x00000000u,0x00000000u,0x00000000u,0x00000000u,
  0x00000000u,0x00000000u,0x00000000u,0x00000000u,0x00000000u,0x00000000u,0x00000000u,0x00000000u,
  0x00000000u,0x00000000u,0x00000000u,0x00000000u,0x00000000u,0x00000000u,0x00000000u,0x00000000u,
  0x00000000u,0x00000000u,0x00000000u,0x00000000u,0x00000000u,0x00000000u,0x00000000u,0x00000000u,
  0xbf0ebec4u,0xbf7bbf6du,0xbf55bf6du,0xbe48bec4u,0xbe480000u,0xbf55bf35u,0xbf7bbf80u,0xbf0ebf35u,
  0x3f0e3ec4u,0x3f7b3f6du,0x3f553f6du,0x3e483ec4u,0x3e480000u,0x3f553f35u,0x3f7b3f80u,0x3f0e3f35u,
  0xbf0ebec4u,0xbf7bbf6du,0xbf55bf6du,0xbe48bec4u,0xbe480000u,0xbf55bf35u,0xbf7bbf80u,0xbf0ebf35u,
  0x3f0e3ec4u,0x3f7b3f6du,0x3f553f6du,0x3e483ec4u,0x3e480000u,0x3f553f35u,0x3f7b3f80u,0x3f0e3f35u,
  0xbec40000u,0xbf6dbf80u,0x3ec40000u,0x3f6d3f80u,0xbf6dbf35u,0xbec4bf35u,0x3f6d3f35u,0x3ec43f35u,
  0xbec40000u,0xbf6dbf80u,0x3ec40000u,0x3f6d3f80u,0xbf6dbf35u,0xbec4bf35u,0x3f6d3f35u,0x3ec43f35u,
  0xbec40000u,0xbf6dbf80u,0x3ec40000u,0x3f6d3f80u,0xbf6dbf35u,0xbec4bf35u,0x3f6d3f35u,0x3ec43f35u,
  0xbec40000u,0xbf6dbf80u,0x3ec40000u,0x3f6d3f80u,0xbf6dbf35u,0xbec4bf35u,0x3f6d3f35u,0x3ec43f35u,
  0x3f7b3f6du,0xbf55bec4u,0x3e48bec4u,0x3f0e3f6du,0x3f0e0000u,0x3e483f35u,0xbf55bf80u,0x3f7b3f35u,
  0xbf7bbf6du,0x3f553ec4u,0xbe483ec4u,0xbf0ebf6du,0xbf0e0000u,0xbe48bf35u,0x3f553f80u,0xbf7bbf35u,
  0x3f7b3f6du,0xbf55bec4u,0x3e48bec4u,0x3f0e3f6du,0x3f0e0000u,0x3e483f35u,0xbf55bf80u,0x3f7b3f35u,
  0xbf7bbf6du,0x3f553ec4u,0xbe483ec4u,0xbf0ebf6du,0xbf0e0000u,0xbe48bf35u,0x3f553f80u,0xbf7bbf35u,
  0xbf350000u,0x3f350000u,0xbf350000u,0x3f350000u,0xbf35bf80u,0x3f353f80u,0xbf35bf80u,0x3f353f80u,
  0xbf350000u,0x3f350000u,0xbf350000u,0x3f350000u,0xbf35bf80u,0x3f353f80u,0xbf35bf80u,0x3f353f80u,
  0xbf350000u,0x3f350000u,0xbf350000u,0x3f350000u,0xbf35bf80u,0x3f353f80u,0xbf35bf80u,0x3f353f80u,
  0xbf350000u,0x3f350000u,0xbf350000u,0x3f350000u,0xbf35bf80u,0x3f353f80u,0xbf35bf80u,0x3f353f80u,
  0xbe48bf6du,0xbf0e3ec4u,0x3f7b3ec4u,0xbf55bf6du,0xbf550000u,0x3f7b3f35u,0xbf0ebf80u,0xbe483f35u,
  0x3e483f6du,0x3f0ebec4u,0xbf7bbec4u,0x3f553f6du,0x3f550000u,0xbf7bbf35u,0x3f0e3f80u,0x3e48bf35u,
  0xbe48bf6du,0xbf0e3ec4u,0x3f7b3ec4u,0xbf55bf6du,0xbf550000u,0x3f7b3f35u,0xbf0ebf80u,0xbe483f35u,
  0x3e483f6du,0x3f0ebec4u,0xbf7bbec4u,0x3f553f6du,0x3f550000u,0xbf7bbf35u,0x3f0e3f80u,0x3e48bf35u,
  0xbf6d0000u,0x3ec43f80u,0x3f6d0000u,0xbec4bf80u,0x3ec4bf35u,0xbf6dbf35u,0xbec43f35u,0x3f6d3f35u,
  0xbf6d0000u,0x3ec43f80u,0x3f6d0000u,0xbec4bf80u,0x3ec4bf35u,0xbf6dbf35u,0xbec43f35u,0x3f6d3f35u,
  0xbf6d0000u,0x3ec43f80u,0x3f6d0000u,0xbec4bf80u,0x3ec4bf35u,0xbf6dbf35u,0xbec43f35u,0x3f6d3f35u,
  0xbf6d0000u,0x3ec43f80u,0x3f6d0000u,0xbec4bf80u,0x3ec4bf35u,0xbf6dbf35u,0xbec43f35u,0x3f6d3f35u,
  0xbf553ec4u,0xbe483f6du,0x3f0e3f6du,0x3f7b3ec4u,0x3f7b0000u,0x3f0ebf35u,0xbe48bf80u,0xbf55bf35u,
  0x3f55bec4u,0x3e48bf6du,0xbf0ebf6du,0xbf7bbec4u,0xbf7b0000u,0xbf0e3f35u,0x3e483f80u,0x3f553f35u,
  0xbf553ec4u,0xbe483f6du,0x3f0e3f6du,0x3f7b3ec4u,0x3f7b0000u,0x3f0ebf35u,0xbe48bf80u,0xbf55bf35u,
  0x3f55bec4u,0x3e48bf6du,0xbf0ebf6du,0xbf7bbec4u,0xbf7b0000u,0xbf0e3f35u,0x3e483f80u,0x3f553f35u,
  0x00003f80u,0x00003f80u,0x00003f80u,0x00003f80u,0x0000bf80u,0x0000bf80u,0x0000bf80u,0x0000bf80u,
  0x00003f80u,0x00003f80u,0x00003f80u,0x00003f80u,0x0000bf80u,0x0000bf80u,0x0000bf80u,0x0000bf80u,
  0x00003f80u,0x00003f80u,0x00003f80u,0x00003f80u,0x0000bf80u,0x0000bf80u,0x0000bf80u,0x0000bf80u,
  0x00003f80u,0x00003f80u,0x00003f80u,0x00003f80u,0x0000bf80u,0x0000bf80u,0x0000bf80u,0x0000bf80u,
  0x3f0ebf6du,0x3f7bbec4u,0x3f553ec4u,0x3e483f6du,0xbe483f80u,0xbf553f35u,0xbf7b0000u,0xbf0ebf35u,
  0xbf0e3f6du,0xbf7b3ec4u,0xbf55bec4u,0xbe48bf6du,0x3e48bf80u,0x3f55bf35u,0x3f7b0000u,0x3f0e3f35u,
  0x3f0ebf6du,0x3f7bbec4u,0x3f553ec4u,0x3e483f6du,0xbe483f80u,0xbf553f35u,0xbf7b0000u,0xbf0ebf35u,
  0xbf0e3f6du,0xbf7b3ec4u,0xbf55bec4u,0xbe48bf6du,0x3e48bf80u,0x3f55bf35u,0x3f7b0000u,0x3f0e3f35u,
  0xbec43f80u,0xbf6d0000u,0x3ec4bf80u,0x3f6d0000u,0x3f6dbf35u,0x3ec43f35u,0xbf6d3f35u,0xbec4bf35u,
  0xbec43f80u,0xbf6d0000u,0x3ec4bf80u,0x3f6d0000u,0x3f6dbf35u,0x3ec43f35u,0xbf6d3f35u,0xbec4bf35u,
  0xbec43f80u,0xbf6d0000u,0x3ec4bf80u,0x3f6d0000u,0x3f6dbf35u,0x3ec43f35u,0xbf6d3f35u,0xbec4bf35u,
  0xbec43f80u,0xbf6d0000u,0x3ec4bf80u,0x3f6d0000u,0x3f6dbf35u,0x3ec43f35u,0xbf6d3f35u,0xbec4bf35u,
  0xbf7b3ec4u,0x3f55bf6du,0xbe483f6du,0xbf0ebec4u,0x3f0ebf80u,0x3e483f35u,0xbf550000u,0x3f7bbf35u,
  0x3f7bbec4u,0xbf553f6du,0x3e48bf6du,0x3f0e3ec4u,0xbf0e3f80u,0xbe48bf35u,0x3f550000u,0xbf7b3f35u,
  0xbf7b3ec4u,0x3f55bf6du,0xbe483f6du,0xbf0ebec4u,0x3f0ebf80u,0x3e483f35u,0xbf550000u,0x3f7bbf35u,
  0x3f7bbec4u,0xbf553f6du,0x3e48bf6du,0x3f0e3ec4u,0xbf0e3f80u,0xbe48bf35u,0x3f550000u,0xbf7b3f35u,
  0xbf353f80u,0x3f35bf80u,0xbf353f80u,0x3f35bf80u,0x3f350000u,0xbf350000u,0x3f350000u,0xbf350000u,
  0xbf353f80u,0x3f35bf80u,0xbf353f80u,0x3f35bf80u,0x3f350000u,0xbf350000u,0x3f350000u,0xbf350000u,
  0xbf353f80u,0x3f35bf80u,0xbf353f80u,0x3f35bf80u,0x3f350000u,0xbf350000u,0x3f350000u,0xbf350000u,
  0xbf353f80u,0x3f35bf80u,0xbf353f80u,0x3f35bf80u,0x3f350000u,0xbf350000u,0x3f350000u,0xbf350000u,
  0x3e483ec4u,0x3f0ebf6du,0xbf7b3f6du,0x3f55bec4u,0xbf553f80u,0x3f7bbf35u,0xbf0e0000u,0xbe483f35u,
  0xbe48bec4u,0xbf0e3f6du,0x3f7bbf6du,0xbf553ec4u,0x3f55bf80u,0xbf7b3f35u,0x3f0e0000u,0x3e48bf35u,
  0x3e483ec4u,0x3f0ebf6du,0xbf7b3f6du,0x3f55bec4u,0xbf553f80u,0x3f7bbf35u,0xbf0e0000u,0xbe483f35u,
  0xbe48bec4u,0xbf0e3f6du,0x3f7bbf6du,0xbf553ec4u,0x3f55bf80u,0xbf7b3f35u,0x3f0e0000u,0x3e48bf35u,
  0xbf6d3f80u,0x3ec40000u,0x3f6dbf80u,0xbec40000u,0xbec43f35u,0x3f6dbf35u,0x3ec4bf35u,0xbf6d3f35u,
  0xbf6d3f80u,0x3ec40000u,0x3f6dbf80u,0xbec40000u,0xbec43f35u,0x3f6dbf35u,0x3ec4bf35u,0xbf6d3f35u,
  0xbf6d3f80u,0x3ec40000u,0x3f6dbf80u,0xbec40000u,0xbec43f35u,0x3f6dbf35u,0x3ec4bf35u,0xbf6d3f35u,
  0xbf6d3f80u,0x3ec40000u,0x3f6dbf80u,0xbec40000u,0xbec43f35u,0x3f6dbf35u,0x3ec4bf35u,0xbf6d3f35u,
  0x3f55bf6du,0x3e48bec4u,0xbf0e3ec4u,0xbf7b3f6du,0x3f7bbf80u,0x3f0ebf35u,0xbe480000u,0xbf553f35u,
  0xbf553f6du,0xbe483ec4u,0x3f0ebec4u,0x3f7bbf6du,0xbf7b3f80u,0xbf0e3f35u,0x3e480000u,0x3f55bf35u,
  0x3f55bf6du,0x3e48bec4u,0xbf0e3ec4u,0xbf7b3f6du,0x3f7bbf80u,0x3f0ebf35u,0xbe480000u,0xbf553f35u,
  0xbf553f6du,0xbe483ec4u,0x3f0ebec4u,0x3f7bbf6du,0xbf7b3f80u,0xbf0e3f35u,0x3e480000u,0x3f55bf35u,
  0xbf800000u,0xbf800000u,0xbf800000u,0xbf800000u,0x3f800000u,0x3f800000u,0x3f800000u,0x3f800000u,
  0xbf800000u,0xbf800000u,0xbf800000u,0xbf800000u,0x3f800000u,0x3f800000u,0x3f800000u,0x3f800000u,
  0xbf800000u,0xbf800000u,0xbf800000u,0xbf800000u,0x3f800000u,0x3f800000u,0x3f800000u,0x3f800000u,
  0xbf800000u,0xbf800000u,0xbf800000u,0xbf800000u,0x3f800000u,0x3f800000u,0x3f800000u,0x3f800000u,
  0x3f553ec4u,0x3e483f6du,0xbf0e3f6du,0xbf7b3ec4u,0xbf7b0000u,0xbf0ebf35u,0x3e48bf80u,0x3f55bf35u,
  0xbf55bec4u,0xbe48bf6du,0x3f0ebf6du,0x3f7bbec4u,0x3f7b0000u,0x3f0e3f35u,0xbe483f80u,0xbf553f35u,
  0x3f553ec4u,0x3e483f6du,0xbf0e3f6du,0xbf7b3ec4u,0xbf7b0000u,0xbf0ebf35u,0x3e48bf80u,0x3f55bf35u,
  0xbf55bec4u,0xbe48bf6du,0x3f0ebf6du,0x3f7bbec4u,0x3f7b0000u,0x3f0e3f35u,0xbe483f80u,0xbf553f35u,
  0xbf6d0000u,0x3ec4bf80u,0x3f6d0000u,0xbec43f80u,0x3ec43f35u,0xbf6d3f35u,0xbec4bf35u,0x3f6dbf35u,
  0xbf6d0000u,0x3ec4bf80u,0x3f6d0000u,0xbec43f80u,0x3ec43f35u,0xbf6d3f35u,0xbec4bf35u,0x3f6dbf35u,
  0xbf6d0000u,0x3ec4bf80u,0x3f6d0000u,0xbec43f80u,0x3ec43f35u,0xbf6d3f35u,0xbec4bf35u,0x3f6dbf35u,
  0xbf6d0000u,0x3ec4bf80u,0x3f6d0000u,0xbec43f80u,0x3ec43f35u,0xbf6d3f35u,0xbec4bf35u,0x3f6dbf35u,
  0x3e48bf6du,0x3f0e3ec4u,0xbf7b3ec4u,0x3f55bf6du,0x3f550000u,0xbf7b3f35u,0x3f0ebf80u,0x3e483f35u,
  0xbe483f6du,0xbf0ebec4u,0x3f7bbec4u,0xbf553f6du,0xbf550000u,0x3f7bbf35u,0xbf0e3f80u,0xbe48bf35u,
  0x3e48bf6du,0x3f0e3ec4u,0xbf7b3ec4u,0x3f55bf6du,0x3f550000u,0xbf7b3f35u,0x3f0ebf80u,0x3e483f35u,
  0xbe483f6du,0xbf0ebec4u,0x3f7bbec4u,0xbf553f6du,0xbf550000u,0x3f7bbf35u,0xbf0e3f80u,0xbe48bf35u,
  0xbf350000u,0x3f350000u,0xbf350000u,0x3f350000u,0xbf353f80u,0x3f35bf80u,0xbf353f80u,0x3f35bf80u,
  0xbf350000u,0x3f350000u,0xbf350000u,0x3f350000u,0xbf353f80u,0x3f35bf80u,0xbf353f80u,0x3f35bf80u,
  0xbf350000u,0x3f350000u,0xbf350000u,0x3f350000u,0xbf353f80u,0x3f35bf80u,0xbf353f80u,0x3f35bf80u,
  0xbf350000u,0x3f350000u,0xbf350000u,0x3f350000u,0xbf353f80u,0x3f35bf80u,0xbf353f80u,0x3f35bf80u,
  0xbf7b3f6du,0x3f55bec4u,0xbe48bec4u,0xbf0e3f6du,0xbf0e0000u,0xbe483f35u,0x3f55bf80u,0xbf7b3f35u,
  0x3f7bbf6du,0xbf553ec4u,0x3e483ec4u,0x3f0ebf6du,0x3f0e0000u,0x3e48bf35u,0xbf553f80u,0x3f7bbf35u,
  0xbf7b3f6du,0x3f55bec4u,0xbe48bec4u,0xbf0e3f6du,0xbf0e0000u,0xbe483f35u,0x3f55bf80u,0xbf7b3f35u,
  0x3f7bbf6du,0xbf553ec4u,0x3e483ec4u,0x3f0ebf6du,0x3f0e0000u,0x3e48bf35u,0xbf553f80u,0x3f7bbf35u,
  0xbec40000u,0xbf6d3f80u,0x3ec40000u,0x3f6dbf80u,0xbf6d3f35u,0xbec43f35u,0x3f6dbf35u,0x3ec4bf35u,
  0xbec40000u,0xbf6d3f80u,0x3ec40000u,0x3f6dbf80u,0xbf6d3f35u,0xbec43f35u,0x3f6dbf35u,0x3ec4bf35u,
  0xbec40000u,0xbf6d3f80u,0x3ec40000u,0x3f6dbf80u,0xbf6d3f35u,0xbec43f35u,0x3f6dbf35u,0x3ec4bf35u,
  0xbec40000u,0xbf6d3f80u,0x3ec40000u,0x3f6dbf80u,0xbf6d3f35u,0xbec43f35u,0x3f6dbf35u,0x3ec4bf35u,
  0x3f0ebec4u,0x3f7bbf6du,0x3f55bf6du,0x3e48bec4u,0x3e480000u,0x3f55bf35u,0x3f7bbf80u,0x3f0ebf35u,
  0xbf0e3ec4u,0xbf7b3f6du,0xbf553f6du,0xbe483ec4u,0xbe480000u,0xbf553f35u,0xbf7b3f80u,0xbf0e3f35u,
  0x3f0ebec4u,0x3f7bbf6du,0x3f55bf6du,0x3e48bec4u,0x3e480000u,0x3f55bf35u,0x3f7bbf80u,0x3f0ebf35u,
  0xbf0e3ec4u,0xbf7b3f6du,0xbf553f6du,0xbe483ec4u,0xbe480000u,0xbf553f35u,0xbf7b3f80u,0xbf0e3f35u,
  0xbf803f80u,0xbf803f80u,0xbf803f80u,0xbf803f80u,0xbf803f80u,0xbf803f80u,0xbf803f80u,0xbf803f80u,
  0xbf803f80u,0xbf803f80u,0xbf803f80u,0xbf803f80u,0xbf803f80u,0xbf803f80u,0xbf803f80u,0xbf803f80u,
  0xbf803f80u,0xbf803f80u,0xbf803f80u,0xbf803f80u,0xbf803f80u,0xbf803f80u,0xbf803f80u,0xbf803f80u,
  0xbf803f80u,0xbf803f80u,0xbf803f80u,0xbf803f80u,0xbf803f80u,0xbf803f80u,0xbf803f80u,0xbf803f80u,
  0xbf553f6du,0xbe483ec4u,0x3f0ebec4u,0x3f7bbf6du,0xbf7b3f80u,0xbf0e3f35u,0x3e480000u,0x3f55bf35u,
  0x3f55bf6du,0x3e48bec4u,0xbf0e3ec4u,0xbf7b3f6du,0x3f7bbf80u,0x3f0ebf35u,0xbe480000u,0xbf553f35u,
  0xbf553f6du,0xbe483ec4u,0x3f0ebec4u,0x3f7bbf6du,0xbf7b3f80u,0xbf0e3f35u,0x3e480000u,0x3f55bf35u,
  0x3f55bf6du,0x3e48bec4u,0xbf0e3ec4u,0xbf7b3f6du,0x3f7bbf80u,0x3f0ebf35u,0xbe480000u,0xbf553f35u,
  0xbf6d3f80u,0x3ec40000u,0x3f6dbf80u,0xbec40000u,0xbec43f35u,0x3f6dbf35u,0x3ec4bf35u,0xbf6d3f35u,
  0xbf6d3f80u,0x3ec40000u,0x3f6dbf80u,0xbec40000u,0xbec43f35u,0x3f6dbf35u,0x3ec4bf35u,0xbf6d3f35u,
  0xbf6d3f80u,0x3ec40000u,0x3f6dbf80u,0xbec40000u,0xbec43f35u,0x3f6dbf35u,0x3ec4bf35u,0xbf6d3f35u,
  0xbf6d3f80u,0x3ec40000u,0x3f6dbf80u,0xbec40000u,0xbec43f35u,0x3f6dbf35u,0x3ec4bf35u,0xbf6d3f35u,
  0xbe48bec4u,0xbf0e3f6du,0x3f7bbf6du,0xbf553ec4u,0x3f55bf80u,0xbf7b3f35u,0x3f0e0000u,0x3e48bf35u,
  0x3e483ec4u,0x3f0ebf6du,0xbf7b3f6du,0x3f55bec4u,0xbf553f80u,0x3f7bbf35u,0xbf0e0000u,0xbe483f35u,
  0xbe48bec4u,0xbf0e3f6du,0x3f7bbf6du,0xbf553ec4u,0x3f55bf80u,0xbf7b3f35u,0x3f0e0000u,0x3e48bf35u,
  0x3e483ec4u,0x3f0ebf6du,0xbf7b3f6du,0x3f55bec4u,0xbf553f80u,0x3f7bbf35u,0xbf0e0000u,0xbe483f35u,
  0xbf353f80u,0x3f35bf80u,0xbf353f80u,0x3f35bf80u,0x3f350000u,0xbf350000u,0x3f350000u,0xbf350000u,
  0xbf353f80u,0x3f35bf80u,0xbf353f80u,0x3f35bf80u,0x3f350000u,0xbf350000u,0x3f350000u,0xbf350000u,
  0xbf353f80u,0x3f35bf80u,0xbf353f80u,0x3f35bf80u,0x3f350000u,0xbf350000u,0x3f350000u,0xbf350000u,
  0xbf353f80u,0x3f35bf80u,0xbf353f80u,0x3f35bf80u,0x3f350000u,0xbf350000u,0x3f350000u,0xbf350000u,
  0x3f7bbec4u,0xbf553f6du,0x3e48bf6du,0x3f0e3ec4u,0xbf0e3f80u,0xbe48bf35u,0x3f550000u,0xbf7b3f35u,
  0xbf7b3ec4u,0x3f55bf6du,0xbe483f6du,0xbf0ebec4u,0x3f0ebf80u,0x3e483f35u,0xbf550000u,0x3f7bbf35u,
  0x3f7bbec4u,0xbf553f6du,0x3e48bf6du,0x3f0e3ec4u,0xbf0e3f80u,0xbe48bf35u,0x3f550000u,0xbf7b3f35u,
  0xbf7b3ec4u,0x3f55bf6du,0xbe483f6du,0xbf0ebec4u,0x3f0ebf80u,0x3e483f35u,0xbf550000u,0x3f7bbf35u,
  0xbec43f80u,0xbf6d0000u,0x3ec4bf80u,0x3f6d0000u,0x3f6dbf35u,0x3ec43f35u,0xbf6d3f35u,0xbec4bf35u,
  0xbec43f80u,0xbf6d0000u,0x3ec4bf80u,0x3f6d0000u,0x3f6dbf35u,0x3ec43f35u,0xbf6d3f35u,0xbec4bf35u,
  0xbec43f80u,0xbf6d0000u,0x3ec4bf80u,0x3f6d0000u,0x3f6dbf35u,0x3ec43f35u,0xbf6d3f35u,0xbec4bf35u,
  0xbec43f80u,0xbf6d0000u,0x3ec4bf80u,0x3f6d0000u,0x3f6dbf35u,0x3ec43f35u,0xbf6d3f35u,0xbec4bf35u,
  0xbf0e3f6du,0xbf7b3ec4u,0xbf55bec4u,0xbe48bf6du,0x3e48bf80u,0x3f55bf35u,0x3f7b0000u,0x3f0e3f35u,
  0x3f0ebf6du,0x3f7bbec4u,0x3f553ec4u,0x3e483f6du,0xbe483f80u,0xbf553f35u,0xbf7b0000u,0xbf0ebf35u,
  0xbf0e3f6du,0xbf7b3ec4u,0xbf55bec4u,0xbe48bf6du,0x3e48bf80u,0x3f55bf35u,0x3f7b0000u,0x3f0e3f35u,
  0x3f0ebf6du,0x3f7bbec4u,0x3f553ec4u,0x3e483f6du,0xbe483f80u,0xbf553f35u,0xbf7b0000u,0xbf0ebf35u,
  0x00000000u,0x00000000u,0x00000000u,0x00000000u,0x00000000u,0x00000000u,0x00000000u,0x00000000u,
  0x00000000u,0x00000000u,0x00000000u,0x00000000u,0x00000000u,0x00000000u,0x00000000u,0x00000000u,
  0x00000000u,0x00000000u,0x00000000u,0x00000000u,0x00000000u,0x00000000u,0x00000000u,0x00000000u,
  0x00000000u,0x00000000u,0x00000000u,0x00000000u,0x00000000u,0x00000000u,0x00000000u,0x00000000u,
  0x3f0ebec4u,0x3f7bbf6du,0x3f55bf6du,0x3e48bec4u,0x3e480000u,0x3f55bf35u,0x3f7bbf80u,0x3f0ebf35u,
  0xbf0e3ec4u,0xbf7b3f6du,0xbf553f6du,0xbe483ec4u,0xbe480000u,0xbf553f35u,0xbf7b3f80u,0xbf0e3f35u,
  0x3f0ebec4u,0x3f7bbf6du,0x3f55bf6du,0x3e48bec4u,0x3e480000u,0x3f55bf35u,0x3f7bbf80u,0x3f0ebf35u,
  0xbf0e3ec4u,0xbf7b3f6du,0xbf553f6du,0xbe483ec4u,0xbe480000u,0xbf553f35u,0xbf7b3f80u,0xbf0e3f35u,
  0x3ec40000u,0x3f6dbf80u,0xbec40000u,0xbf6d3f80u,0x3f6dbf35u,0x3ec4bf35u,0xbf6d3f35u,0xbec43f35u,
  0x3ec40000u,0x3f6dbf80u,0xbec40000u,0xbf6d3f80u,0x3f6dbf35u,0x3ec4bf35u,0xbf6d3f35u,0xbec43f35u,
  0x3ec40000u,0x3f6dbf80u,0xbec40000u,0xbf6d3f80u,0x3f6dbf35u,0x3ec4bf35u,0xbf6d3f35u,0xbec43f35u,
  0x3ec40000u,0x3f6dbf80u,0xbec40000u,0xbf6d3f80u,0x3f6dbf35u,0x3ec4bf35u,0xbf6d3f35u,0xbec43f35u,
  0xbf7b3f6du,0x3f55bec4u,0xbe48bec4u,0xbf0e3f6du,0xbf0e0000u,0xbe483f35u,0x3f55bf80u,0xbf7b3f35u,
  0x3f7bbf6du,0xbf553ec4u,0x3e483ec4u,0x3f0ebf6du,0x3f0e0000u,0x3e48bf35u,0xbf553f80u,0x3f7bbf35u,
  0xbf7b3f6du,0x3f55bec4u,0xbe48bec4u,0xbf0e3f6du,0xbf0e0000u,0xbe483f35u,0x3f55bf80u,0xbf7b3f35u,
  0x3f7bbf6du,0xbf553ec4u,0x3e483ec4u,0x3f0ebf6du,0x3f0e0000u,0x3e48bf35u,0xbf553f80u,0x3f7bbf35u,
  0x3f350000u,0xbf350000u,0x3f350000u,0xbf350000u,0x3f35bf80u,0xbf353f80u,0x3f35bf80u,0xbf353f80u,
  0x3f350000u,0xbf350000u,0x3f350000u,0xbf350000u,0x3f35bf80u,0xbf353f80u,0x3f35bf80u,0xbf353f80u,
  0x3f350000u,0xbf350000u,0x3f350000u,0xbf350000u,0x3f35bf80u,0xbf353f80u,0x3f35bf80u,0xbf353f80u,
  0x3f350000u,0xbf350000u,0x3f350000u,0xbf350000u,0x3f35bf80u,0xbf353f80u,0x3f35bf80u,0xbf353f80u,
  0x3e48bf6du,0x3f0e3ec4u,0xbf7b3ec4u,0x3f55bf6du,0x3f550000u,0xbf7b3f35u,0x3f0ebf80u,0x3e483f35u,
  0xbe483f6du,0xbf0ebec4u,0x3f7bbec4u,0xbf553f6du,0xbf550000u,0x3f7bbf35u,0xbf0e3f80u,0xbe48bf35u,
  0x3e48bf6du,0x3f0e3ec4u,0xbf7b3ec4u,0x3f55bf6du,0x3f550000u,0xbf7b3f35u,0x3f0ebf80u,0x3e483f35u,
  0xbe483f6du,0xbf0ebec4u,0x3f7bbec4u,0xbf553f6du,0xbf550000u,0x3f7bbf35u,0xbf0e3f80u,0xbe48bf35u,
  0x3f6d0000u,0xbec43f80u,0xbf6d0000u,0x3ec4bf80u,0xbec4bf35u,0x3f6dbf35u,0x3ec43f35u,0xbf6d3f35u,
  0x3f6d0000u,0xbec43f80u,0xbf6d0000u,0x3ec4bf80u,0xbec4bf35u,0x3f6dbf35u,0x3ec43f35u,0xbf6d3f35u,
  0x3f6d0000u,0xbec43f80u,0xbf6d0000u,0x3ec4bf80u,0xbec4bf35u,0x3f6dbf35u,0x3ec43f35u,0xbf6d3f35u,
  0x3f6d0000u,0xbec43f80u,0xbf6d0000u,0x3ec4bf80u,0xbec4bf35u,0x3f6dbf35u,0x3ec43f35u,0xbf6d3f35u,
  0x3f553ec4u,0x3e483f6du,0xbf0e3f6du,0xbf7b3ec4u,0xbf7b0000u,0xbf0ebf35u,0x3e48bf80u,0x3f55bf35u,
  0xbf55bec4u,0xbe48bf6du,0x3f0ebf6du,0x3f7bbec4u,0x3f7b0000u,0x3f0e3f35u,0xbe483f80u,0xbf553f35u,
  0x3f553ec4u,0x3e483f6du,0xbf0e3f6du,0xbf7b3ec4u,0xbf7b0000u,0xbf0ebf35u,0x3e48bf80u,0x3f55bf35u,
  0xbf55bec4u,0xbe48bf6du,0x3f0ebf6du,0x3f7bbec4u,0x3f7b0000u,0x3f0e3f35u,0xbe483f80u,0xbf553f35u,
  0x00003f80u,0x00003f80u,0x00003f80u,0x00003f80u,0x0000bf80u,0x0000bf80u,0x0000bf80u,0x0000bf80u,
  0x00003f80u,0x00003f80u,0x00003f80u,0x00003f80u,0x0000bf80u,0x0000bf80u,0x0000bf80u,0x0000bf80u,
  0x00003f80u,0x00003f80u,0x00003f80u,0x00003f80u,0x0000bf80u,0x0000bf80u,0x0000bf80u,0x0000bf80u,
  0x00003f80u,0x00003f80u,0x00003f80u,0x00003f80u,0x0000bf80u,0x0000bf80u,0x0000bf80u,0x0000bf80u,
  0xbf0ebf6du,0xbf7bbec4u,0xbf553ec4u,0xbe483f6du,0x3e483f80u,0x3f553f35u,0x3f7b0000u,0x3f0ebf35u,
  0x3f0e3f6du,0x3f7b3ec4u,0x3f55bec4u,0x3e48bf6du,0xbe48bf80u,0xbf55bf35u,0xbf7b0000u,0xbf0e3f35u,
  0xbf0ebf6du,0xbf7bbec4u,0xbf553ec4u,0xbe483f6du,0x3e483f80u,0x3f553f35u,0x3f7b0000u,0x3f0ebf35u,
  0x3f0e3f6du,0x3f7b3ec4u,0x3f55bec4u,0x3e48bf6du,0xbe48bf80u,0xbf55bf35u,0xbf7b0000u,0xbf0e3f35u,
  0x3ec43f80u,0x3f6d0000u,0xbec4bf80u,0xbf6d0000u,0xbf6dbf35u,0xbec43f35u,0x3f6d3f35u,0x3ec4bf35u,
  0x3ec43f80u,0x3f6d0000u,0xbec4bf80u,0xbf6d0000u,0xbf6dbf35u,0xbec43f35u,0x3f6d3f35u,0x3ec4bf35u,
  0x3ec43f80u,0x3f6d0000u,0xbec4bf80u,0xbf6d0000u,0xbf6dbf35u,0xbec43f35u,0x3f6d3f35u,0x3ec4bf35u,
  0x3ec43f80u,0x3f6d0000u,0xbec4bf80u,0xbf6d0000u,0xbf6dbf35u,0xbec43f35u,0x3f6d3f35u,0x3ec4bf35u,
  0x3f7b3ec4u,0xbf55bf6du,0x3e483f6du,0x3f0ebec4u,0xbf0ebf80u,0xbe483f35u,0x3f550000u,0xbf7bbf35u,
  0xbf7bbec4u,0x3f553f6du,0xbe48bf6du,0xbf0e3ec4u,0x3f0e3f80u,0x3e48bf35u,0xbf550000u,0x3f7b3f35u,
  0x3f7b3ec4u,0xbf55bf6du,0x3e483f6du,0x3f0ebec4u,0xbf0ebf80u,0xbe483f35u,0x3f550000u,0xbf7bbf35u,
  0xbf7bbec4u,0x3f553f6du,0xbe48bf6du,0xbf0e3ec4u,0x3f0e3f80u,0x3e48bf35u,0xbf550000u,0x3f7b3f35u,
  0x3f353f80u,0xbf35bf80u,0x3f353f80u,0xbf35bf80u,0xbf350000u,0x3f350000u,0xbf350000u,0x3f350000u,
  0x3f353f80u,0xbf35bf80u,0x3f353f80u,0xbf35bf80u,0xbf350000u,0x3f350000u,0xbf350000u,0x3f350000u,
  0x3f353f80u,0xbf35bf80u,0x3f353f80u,0xbf35bf80u,0xbf350000u,0x3f350000u,0xbf350000u,0x3f350000u,
  0x3f353f80u,0xbf35bf80u,0x3f353f80u,0xbf35bf80u,0xbf350000u,0x3f350000u,0xbf350000u,0x3f350000u,
  0xbe483ec4u,0xbf0ebf6du,0x3f7b3f6du,0xbf55bec4u,0x3f553f80u,0xbf7bbf35u,0x3f0e0000u,0x3e483f35u,
  0x3e48bec4u,0x3f0e3f6du,0xbf7bbf6du,0x3f553ec4u,0xbf55bf80u,0x3f7b3f35u,0xbf0e0000u,0xbe48bf35u,
  0xbe483ec4u,0xbf0ebf6du,0x3f7b3f6du,0xbf55bec4u,0x3f553f80u,0xbf7bbf35u,0x3f0e0000u,0x3e483f35u,
  0x3e48bec4u,0x3f0e3f6du,0xbf7bbf6du,0x3f553ec4u,0xbf55bf80u,0x3f7b3f35u,0xbf0e0000u,0xbe48bf35u,
  0x3f6d3f80u,0xbec40000u,0xbf6dbf80u,0x3ec40000u,0x3ec43f35u,0xbf6dbf35u,0xbec4bf35u,0x3f6d3f35u,
  0x3f6d3f80u,0xbec40000u,0xbf6dbf80u,0x3ec40000u,0x3ec43f35u,0xbf6dbf35u,0xbec4bf35u,0x3f6d3f35u,
  0x3f6d3f80u,0xbec40000u,0xbf6dbf80u,0x3ec40000u,0x3ec43f35u,0xbf6dbf35u,0xbec4bf35u,0x3f6d3f35u,
  0x3f6d3f80u,0xbec40000u,0xbf6dbf80u,0x3ec40000u,0x3ec43f35u,0xbf6dbf35u,0xbec4bf35u,0x3f6d3f35u,
  0xbf55bf6du,0xbe48bec4u,0x3f0e3ec4u,0x3f7b3f6du,0xbf7bbf80u,0xbf0ebf35u,0x3e480000u,0x3f553f35u,
  0x3f553f6du,0x3e483ec4u,0xbf0ebec4u,0xbf7bbf6du,0x3f7b3f80u,0x3f0e3f35u,0xbe480000u,0xbf55bf35u,
  0xbf55bf6du,0xbe48bec4u,0x3f0e3ec4u,0x3f7b3f6du,0xbf7bbf80u,0xbf0ebf35u,0x3e480000u,0x3f553f35u,
  0x3f553f6du,0x3e483ec4u,0xbf0ebec4u,0xbf7bbf6du,0x3f7b3f80u,0x3f0e3f35u,0xbe480000u,0xbf55bf35u,
  0x3f800000u,0x3f800000u,0x3f800000u,0x3f800000u,0xbf800000u,0xbf800000u,0xbf800000u,0xbf800000u,
  0x3f800000u,0x3f800000u,0x3f800000u,0x3f800000u,0xbf800000u,0xbf800000u,0xbf800000u,0xbf800000u,
  0x3f800000u,0x3f800000u,0x3f800000u,0x3f800000u,0xbf800000u,0xbf800000u,0xbf800000u,0xbf800000u,
  0x3f800000u,0x3f800000u,0x3f800000u,0x3f800000u,0xbf800000u,0xbf800000u,0xbf800000u,0xbf800000u,
  0xbf553ec4u,0xbe483f6du,0x3f0e3f6du,0x3f7b3ec4u,0x3f7b0000u,0x3f0ebf35u,0xbe48bf80u,0xbf55bf35u,
  0x3f55bec4u,0x3e48bf6du,0xbf0ebf6du,0xbf7bbec4u,0xbf7b0000u,0xbf0e3f35u,0x3e483f80u,0x3f553f35u,
  0xbf553ec4u,0xbe483f6du,0x3f0e3f6du,0x3f7b3ec4u,0x3f7b0000u,0x3f0ebf35u,0xbe48bf80u,0xbf55bf35u,
  0x3f55bec4u,0x3e48bf6du,0xbf0ebf6du,0xbf7bbec4u,0xbf7b0000u,0xbf0e3f35u,0x3e483f80u,0x3f553f35u,
  0x3f6d0000u,0xbec4bf80u,0xbf6d0000u,0x3ec43f80u,0xbec43f35u,0x3f6d3f35u,0x3ec4bf35u,0xbf6dbf35u,
  0x3f6d0000u,0xbec4bf80u,0xbf6d0000u,0x3ec43f80u,0xbec43f35u,0x3f6d3f35u,0x3ec4bf35u,0xbf6dbf35u,
  0x3f6d0000u,0xbec4bf80u,0xbf6d0000u,0x3ec43f80u,0xbec43f35u,0x3f6d3f35u,0x3ec4bf35u,0xbf6dbf35u,
  0x3f6d0000u,0xbec4bf80u,0xbf6d0000u,0x3ec43f80u,0xbec43f35u,0x3f6d3f35u,0x3ec4bf35u,0xbf6dbf35u,
  0xbe48bf6du,0xbf0e3ec4u,0x3f7b3ec4u,0xbf55bf6du,0xbf550000u,0x3f7b3f35u,0xbf0ebf80u,0xbe483f35u,
  0x3e483f6du,0x3f0ebec4u,0xbf7bbec4u,0x3f553f6du,0x3f550000u,0xbf7bbf35u,0x3f0e3f80u,0x3e48bf35u,
  0xbe48bf6du,0xbf0e3ec4u,0x3f7b3ec4u,0xbf55bf6du,0xbf550000u,0x3f7b3f35u,0xbf0ebf80u,0xbe483f35u,
  0x3e483f6du,0x3f0ebec4u,0xbf7bbec4u,0x3f553f6du,0x3f550000u,0xbf7bbf35u,0x3f0e3f80u,0x3e48bf35u,
  0x3f350000u,0xbf350000u,0x3f350000u,0xbf350000u,0x3f353f80u,0xbf35bf80u,0x3f353f80u,0xbf35bf80u,
  0x3f350000u,0xbf350000u,0x3f350000u,0xbf350000u,0x3f353f80u,0xbf35bf80u,0x3f353f80u,0xbf35bf80u,
  0x3f350000u,0xbf350000u,0x3f350000u,0xbf350000u,0x3f353f80u,0xbf35bf80u,0x3f353f80u,0xbf35bf80u,
  0x3f350000u,0xbf350000u,0x3f350000u,0xbf350000u,0x3f353f80u,0xbf35bf80u,0x3f353f80u,0xbf35bf80u,
  0x3f7b3f6du,0xbf55bec4u,0x3e48bec4u,0x3f0e3f6du,0x3f0e0000u,0x3e483f35u,0xbf55bf80u,0x3f7b3f35u,
  0xbf7bbf6du,0x3f553ec4u,0xbe483ec4u,0xbf0ebf6du,0xbf0e0000u,0xbe48bf35u,0x3f553f80u,0xbf7bbf35u,
  0x3f7b3f6du,0xbf55bec4u,0x3e48bec4u,0x3f0e3f6du,0x3f0e0000u,0x3e483f35u,0xbf55bf80u,0x3f7b3f35u,
  0xbf7bbf6du,0x3f553ec4u,0xbe483ec4u,0xbf0ebf6du,0xbf0e0000u,0xbe48bf35u,0x3f553f80u,0xbf7bbf35u,
  0x3ec40000u,0x3f6d3f80u,0xbec40000u,0xbf6dbf80u,0x3f6d3f35u,0x3ec43f35u,0xbf6dbf35u,0xbec4bf35u,
  0x3ec40000u,0x3f6d3f80u,0xbec40000u,0xbf6dbf80u,0x3f6d3f35u,0x3ec43f35u,0xbf6dbf35u,0xbec4bf35u,
  0x3ec40000u,0x3f6d3f80u,0xbec40000u,0xbf6dbf80u,0x3f6d3f35u,0x3ec43f35u,0xbf6dbf35u,0xbec4bf35u,
  0x3ec40000u,0x3f6d3f80u,0xbec40000u,0xbf6dbf80u,0x3f6d3f35u,0x3ec43f35u,0xbf6dbf35u,0xbec4bf35u,
  0xbf0ebec4u,0xbf7bbf6du,0xbf55bf6du,0xbe48bec4u,0xbe480000u,0xbf55bf35u,0xbf7bbf80u,0xbf0ebf35u,
  0x3f0e3ec4u,0x3f7b3f6du,0x3f553f6du,0x3e483ec4u,0x3e480000u,0x3f553f35u,0x3f7b3f80u,0x3f0e3f35u,
  0xbf0ebec4u,0xbf7bbf6du,0xbf55bf6du,0xbe48bec4u,0xbe480000u,0xbf55bf35u,0xbf7bbf80u,0xbf0ebf35u,
  0x3f0e3ec4u,0x3f7b3f6du,0x3f553f6du,0x3e483ec4u,0x3e480000u,0x3f553f35u,0x3f7b3f80u,0x3f0e3f35u,
  0x3f7f3f80u,0x3f623f6du,0x3f223f35u,0x3e953ec4u,0x3f753f7bu,0x3f463f55u,0x3ef13f0eu,0x3dc93e48u,
  0xbdc90000u,0xbef1bec4u,0xbf46bf35u,0xbf75bf6du,0xbe95be48u,0xbf22bf0eu,0xbf62bf55u,0xbf7fbf7bu,
  0xbf7fbf80u,0xbf62bf6du,0xbf22bf35u,0xbe95bec4u,0xbf75bf7bu,0xbf46bf55u,0xbef1bf0eu,0xbdc9be48u,
  0x3dc90000u,0x3ef13ec4u,0x3f463f35u,0x3f753f6du,0x3e953e48u,0x3f223f0eu,0x3f623f55u,0x3f7f3f7bu,
  0x3f223f55u,0xbef1be48u,0xbf7fbf7bu,0xbe95bf0eu,0x3f753f80u,0x3dc93ec4u,0xbf62bf35u,0xbf46bf6du,
  0x3f463f0eu,0x3f623f7bu,0xbdc93e48u,0xbf75bf55u,0x3e950000u,0x3f7f3f6du,0x3ef13f35u,0xbf22bec4u,
  0xbf22bf55u,0x3ef13e48u,0x3f7f3f7bu,0x3e953f0eu,0xbf75bf80u,0xbdc9bec4u,0x3f623f35u,0x3f463f6du,
  0xbf46bf0eu,0xbf62bf7bu,0x3dc9be48u,0x3f753f55u,0xbe950000u,0xbf7fbf6du,0xbef1bf35u,0x3f223ec4u,
  0xbef10000u,0xbf22bf6du,0x3f753f35u,0xbdc93ec4u,0xbf7fbf55u,0x3e95be48u,0x3f463f7bu,0xbf62bf0eu,
  0x3f623f80u,0xbf46bec4u,0xbe95bf35u,0x3f7f3f6du,0x3dc93f0eu,0xbf75bf7bu,0x3f223e48u,0x3ef13f55u,
  0x3ef10000u,0x3f223f6du,0xbf75bf35u,0x3dc9bec4u,0x3f7f3f55u,0xbe953e48u,0xbf46bf7bu,0x3f623f0eu,
  0xbf62bf80u,0x3f463ec4u,0x3e953f35u,0xbf7fbf6du,0xbdc9bf0eu,0x3f753f7bu,0xbf22be48u,0xbef1bf55u,
  0x3f623f7bu,0xbf7fbf55u,0x3f753f0eu,0xbf46be48u,0x3f220000u,0xbe953ec4u,0xbdc9bf35u,0x3ef13f6du,
  0xbef13e48u,0x3dc9bf0eu,0x3e953f55u,0xbf22bf7bu,0x3f463f80u,0xbf75bf6du,0x3f7f3f35u,0xbf62bec4u,
  0xbf62bf7bu,0x3f7f3f55u,0xbf75bf0eu,0x3f463e48u,0xbf220000u,0x3e95bec4u,0x3dc93f35u,0xbef1bf6du,
  0x3ef1be48u,0xbdc93f0eu,0xbe95bf55u,0x3f223f7bu,0xbf46bf80u,0x3f753f6du,0xbf7fbf35u,0x3f623ec4u,
  0xbf22bf80u,0x3e953f6du,0x3dc9bf35u,0xbef13ec4u,0x3f623e48u,0xbf7fbf0eu,0x3f753f55u,0xbf46bf7bu,
  0x3f460000u,0xbf75bec4u,0x3f7f3f35u,0xbf62bf6du,0x3ef13f7bu,0xbdc9bf55u,0xbe953f0eu,0x3f22be48u,
  0x3f223f80u,0xbe95bf6du,0xbdc93f35u,0x3ef1bec4u,0xbf62be48u,0x3f7f3f0eu,0xbf75bf55u,0x3f463f7bu,
  0xbf460000u,0x3f753ec4u,0xbf7fbf35u,0x3f623f6du,0xbef1bf7bu,0x3dc93f55u,0x3e95bf0eu,0xbf223e48u,
  0x3f7f3f0eu,0xbe95bf7bu,0xbf463e48u,0x3f623f55u,0xbef1bf80u,0xbf223ec4u,0x3f753f35u,0xbdc9bf6du,
  0x3dc9bf55u,0xbf75be48u,0x3f223f7bu,0x3ef1bf0eu,0xbf620000u,0x3f463f6du,0x3e95bf35u,0xbf7fbec4u,
  0xbf7fbf0eu,0x3e953f7bu,0x3f46be48u,0xbf62bf55u,0x3ef13f80u,0x3f22bec4u,0xbf75bf35u,0x3dc93f6du,
  0xbdc93f55u,0x3f753e48u,0xbf22bf7bu,0xbef13f0eu,0x3f620000u,0xbf46bf6du,0xbe953f35u,0x3f7f3ec4u,
  0x3f750000u,0x3dc9bf6du,0xbf62bf35u,0xbf463ec4u,0xbf223f0eu,0x3ef13f7bu,0x3f7f3e48u,0x3e95bf55u,
  0xbe95bf80u,0xbf7fbec4u,0xbef13f35u,0x3f223f6du,0x3f463f55u,0x3f62be48u,0xbdc9bf7bu,0xbf75bf0eu,
  0xbf750000u,0xbdc93f6du,0x3f623f35u,0x3f46bec4u,0x3f22bf0eu,0xbef1bf7bu,0xbf7fbe48u,0xbe953f55u,
  0x3e953f80u,0x3f7f3ec4u,0x3ef1bf35u,0xbf22bf6du,0xbf46bf55u,0xbf623e48u,0x3dc93f7bu,0x3f753f0eu,
  0x3f75be48u,0x3f46bf0eu,0x3ef1bf55u,0x3dc9bf7bu,0xbf7f0000u,0xbf623ec4u,0xbf223f35u,0xbe953f6du,
  0x3e953f7bu,0x3f223f55u,0x3f623f0eu,0x3f7f3e48u,0xbdc9bf80u,0xbef1bf6du,0xbf46bf35u,0xbf75bec4u,
  0xbf753e48u,0xbf463f0eu,0xbef13f55u,0xbdc93f7bu,0x3f7f0000u,0x3f62bec4u,0x3f22bf35u,0x3e95bf6du,
  0xbe95bf7bu,0xbf22bf55u,0xbf62bf0eu,0xbf7fbe48u,0x3dc93f80u,0x3ef13f6du,0x3f463f35u,0x3f753ec4u,
  0xbdc90000u,0xbef1bec4u,0xbf46bf35u,0xbf75bf6du,0xbe95be48u,0xbf22bf0eu,0xbf62bf55u,0xbf7fbf7bu,
  0xbf7fbf80u,0xbf62bf6du,0xbf22bf35u,0xbe95bec4u,0xbf75bf7bu,0xbf46bf55u,0xbef1bf0eu,0xbdc9be48u,
  0x3dc90000u,0x3ef13ec4u,0x3f463f35u,0x3f753f6du,0x3e953e48u,0x3f223f0eu,0x3f623f55u,0x3f7f3f7bu,
  0x3f7f3f80u,0x3f623f6du,0x3f223f35u,0x3e953ec4u,0x3f753f7bu,0x3f463f55u,0x3ef13f0eu,0x3dc93e48u,
  0xbf46bf0eu,0xbf62bf7bu,0x3dc9be48u,0x3f753f55u,0xbe950000u,0xbf7fbf6du,0xbef1bf35u,0x3f223ec4u,
  0x3f223f55u,0xbef1be48u,0xbf7fbf7bu,0xbe95bf0eu,0x3f753f80u,0x3dc93ec4u,0xbf62bf35u,0xbf46bf6du,
  0x3f463f0eu,0x3f623f7bu,0xbdc93e48u,0xbf75bf55u,0x3e950000u,0x3f7f3f6du,0x3ef13f35u,0xbf22bec4u,
  0xbf22bf55u,0x3ef13e48u,0x3f7f3f7bu,0x3e953f0eu,0xbf75bf80u,0xbdc9bec4u,0x3f623f35u,0x3f463f6du,
  0xbf62bf80u,0x3f463ec4u,0x3e953f35u,0xbf7fbf6du,0xbdc9bf0eu,0x3f753f7bu,0xbf22be48u,0xbef1bf55u,
  0xbef10000u,0xbf22bf6du,0x3f753f35u,0xbdc93ec4u,0xbf7fbf55u,0x3e95be48u,0x3f463f7bu,0xbf62bf0eu,
  0x3f623f80u,0xbf46bec4u,0xbe95bf35u,0x3f7f3f6du,0x3dc93f0eu,0xbf75bf7bu,0x3f223e48u,0x3ef13f55u,
  0x3ef10000u,0x3f223f6du,0xbf75bf35u,0x3dc9bec4u,0x3f7f3f55u,0xbe953e48u,0xbf46bf7bu,0x3f623f0eu,
  0xbef13e48u,0x3dc9bf0eu,0x3e953f55u,0xbf22bf7bu,0x3f463f80u,0xbf75bf6du,0x3f7f3f35u,0xbf62bec4u,
  0xbf62bf7bu,0x3f7f3f55u,0xbf75bf0eu,0x3f463e48u,0xbf220000u,0x3e95bec4u,0x3dc93f35u,0xbef1bf6du,
  0x3ef1be48u,0xbdc93f0eu,0xbe95bf55u,0x3f223f7bu,0xbf46bf80u,0x3f753f6du,0xbf7fbf35u,0x3f623ec4u,
  0x3f623f7bu,0xbf7fbf55u,0x3f753f0eu,0xbf46be48u,0x3f220000u,0xbe953ec4u,0xbdc9bf35u,0x3ef13f6du,
  0x3f460000u,0xbf75bec4u,0x3f7f3f35u,0xbf62bf6du,0x3ef13f7bu,0xbdc9bf55u,0xbe953f0eu,0x3f22be48u,
  0x3f223f80u,0xbe95bf6du,0xbdc93f35u,0x3ef1bec4u,0xbf62be48u,0x3f7f3f0eu,0xbf75bf55u,0x3f463f7bu,
  0xbf460000u,0x3f753ec4u,0xbf7fbf35u,0x3f623f6du,0xbef1bf7bu,0x3dc93f55u,0x3e95bf0eu,0xbf223e48u,
  0xbf22bf80u,0x3e953f6du,0x3dc9bf35u,0xbef13ec4u,0x3f623e48u,0xbf7fbf0eu,0x3f753f55u,0xbf46bf7bu,
  0xbdc93f55u,0x3f753e48u,0xbf22bf7bu,0xbef13f0eu,0x3f620000u,0xbf46bf6du,0xbe953f35u,0x3f7f3ec4u,
  0x3f7f3f0eu,0xbe95bf7bu,0xbf463e48u,0x3f623f55u,0xbef1bf80u,0xbf223ec4u,0x3f753f35u,0xbdc9bf6du,
  0x3dc9bf55u,0xbf75be48u,0x3f223f7bu,0x3ef1bf0eu,0xbf620000u,0x3f463f6du,0x3e95bf35u,0xbf7fbec4u,
  0xbf7fbf0eu,0x3e953f7bu,0x3f46be48u,0xbf62bf55u,0x3ef13f80u,0x3f22bec4u,0xbf75bf35u,0x3dc93f6du,
  0x3e953f80u,0x3f7f3ec4u,0x3ef1bf35u,0xbf22bf6du,0xbf46bf55u,0xbf623e48u,0x3dc93f7bu,0x3f753f0eu,
  0x3f750000u,0x3dc9bf6du,0xbf62bf35u,0xbf463ec4u,0xbf223f0eu,0x3ef13f7bu,0x3f7f3e48u,0x3e95bf55u,
  0xbe95bf80u,0xbf7fbec4u,0xbef13f35u,0x3f223f6du,0x3f463f55u,0x3f62be48u,0xbdc9bf7bu,0xbf75bf0eu,
  0xbf750000u,0xbdc93f6du,0x3f623f35u,0x3f46bec4u,0x3f22bf0eu,0xbef1bf7bu,0xbf7fbe48u,0xbe953f55u,
  0x3e953f7bu,0x3f223f55u,0x3f623f0eu,0x3f7f3e48u,0xbdc9bf80u,0xbef1bf6du,0xbf46bf35u,0xbf75bec4u,
  0xbf753e48u,0xbf463f0eu,0xbef13f55u,0xbdc93f7bu,0x3f7f0000u,0x3f62bec4u,0x3f22bf35u,0x3e95bf6du,
  0xbe95bf7bu,0xbf22bf55u,0xbf62bf0eu,0xbf7fbe48u,0x3dc93f80u,0x3ef13f6du,0x3f463f35u,0x3f753ec4u,
  0x3f75be48u,0x3f46bf0eu,0x3ef1bf55u,0x3dc9bf7bu,0xbf7f0000u,0xbf623ec4u,0xbf223f35u,0xbe953f6du,
  0xbdc93f80u,0xbef13f6du,0xbf463f35u,0xbf753ec4u,0x3e95bf7bu,0x3f22bf55u,0x3f62bf0eu,0x3f7fbe48u,
  0xbf7f0000u,0xbf62bec4u,0xbf22bf35u,0xbe95bf6du,0x3f753e48u,0x3f463f0eu,0x3ef13f55u,0x3dc93f7bu,
  0x3dc9bf80u,0x3ef1bf6du,0x3f46bf35u,0x3f75bec4u,0xbe953f7bu,0xbf223f55u,0xbf623f0eu,0xbf7f3e48u,
  0x3f7f0000u,0x3f623ec4u,0x3f223f35u,0x3e953f6du,0xbf75be48u,0xbf46bf0eu,0xbef1bf55u,0xbdc9bf7bu,
  0x3f46bf55u,0x3f623e48u,0xbdc93f7bu,0xbf753f0eu,0xbe953f80u,0xbf7f3ec4u,0xbef1bf35u,0x3f22bf6du,
  0xbf22bf0eu,0x3ef1bf7bu,0x3f7fbe48u,0x3e953f55u,0x3f750000u,0x3dc93f6du,0xbf623f35u,0xbf46bec4u,
  0xbf463f55u,0xbf62be48u,0x3dc9bf7bu,0x3f75bf0eu,0x3e95bf80u,0x3f7fbec4u,0x3ef13f35u,0xbf223f6du,
  0x3f223f0eu,0xbef13f7bu,0xbf7f3e48u,0xbe95bf55u,0xbf750000u,0xbdc9bf6du,0x3f62bf35u,0x3f463ec4u,
  0xbf620000u,0x3f46bf6du,0x3e953f35u,0xbf7f3ec4u,0x3dc93f55u,0xbf753e48u,0x3f22bf7bu,0x3ef13f0eu,
  0xbef13f80u,0xbf22bec4u,0x3f75bf35u,0xbdc93f6du,0x3f7fbf0eu,0xbe953f7bu,0xbf46be48u,0x3f62bf55u,
  0x3f620000u,0xbf463f6du,0xbe95bf35u,0x3f7fbec4u,0xbdc9bf55u,0x3f75be48u,0xbf223f7bu,0xbef1bf0eu,
  0x3ef1bf80u,0x3f223ec4u,0xbf753f35u,0x3dc9bf6du,0xbf7f3f0eu,0x3e95bf7bu,0x3f463e48u,0xbf623f55u,
  0x3ef1bf7bu,0xbdc93f55u,0xbe95bf0eu,0x3f223e48u,0x3f460000u,0xbf753ec4u,0x3f7fbf35u,0xbf623f6du,
  0x3f62be48u,0xbf7f3f0eu,0x3f75bf55u,0xbf463f7bu,0xbf223f80u,0x3e95bf6du,0x3dc93f35u,0xbef1bec4u,
  0xbef13f7bu,0x3dc9bf55u,0x3e953f0eu,0xbf22be48u,0xbf460000u,0x3f75bec4u,0xbf7f3f35u,0x3f62bf6du,
  0xbf623e48u,0x3f7fbf0eu,0xbf753f55u,0x3f46bf7bu,0x3f22bf80u,0xbe953f6du,0xbdc9bf35u,0x3ef13ec4u,
  0x3f46bf80u,0xbf753f6du,0x3f7fbf35u,0xbf623ec4u,0xbef1be48u,0x3dc93f0eu,0x3e95bf55u,0xbf223f7bu,
  0x3f220000u,0xbe95bec4u,0xbdc93f35u,0x3ef1bf6du,0x3f62bf7bu,0xbf7f3f55u,0x3f75bf0eu,0xbf463e48u,
  0xbf463f80u,0x3f75bf6du,0xbf7f3f35u,0x3f62bec4u,0x3ef13e48u,0xbdc9bf0eu,0xbe953f55u,0x3f22bf7bu,
  0xbf220000u,0x3e953ec4u,0x3dc9bf35u,0xbef13f6du,0xbf623f7bu,0x3f7fbf55u,0xbf753f0eu,0x3f46be48u,
  0x3dc9bf0eu,0xbf753f7bu,0x3f22be48u,0x3ef1bf55u,0x3f62bf80u,0xbf463ec4u,0xbe953f35u,0x3f7fbf6du,
  0xbf7f3f55u,0x3e953e48u,0x3f46bf7bu,0xbf623f0eu,0xbef10000u,0xbf223f6du,0x3f75bf35u,0xbdc9bec4u,
  0xbdc93f0eu,0x3f75bf7bu,0xbf223e48u,0xbef13f55u,0xbf623f80u,0x3f46bec4u,0x3e95bf35u,0xbf7f3f6du,
  0x3f7fbf55u,0xbe95be48u,0xbf463f7bu,0x3f62bf0eu,0x3ef10000u,0x3f22bf6du,0xbf753f35u,0x3dc93ec4u,
  0x3e950000u,0x3f7fbf6du,0x3ef1bf35u,0xbf223ec4u,0x3f46bf0eu,0x3f62bf7bu,0xbdc9be48u,0xbf753f55u,
  0x3f75bf80u,0x3dc9bec4u,0xbf623f35u,0xbf463f6du,0x3f22bf55u,0xbef13e48u,0xbf7f3f7bu,0xbe953f0eu,
  0xbe950000u,0xbf7f3f6du,0xbef13f35u,0x3f22bec4u,0xbf463f0eu,0xbf623f7bu,0x3dc93e48u,0x3f75bf55u,
  0xbf753f80u,0xbdc93ec4u,0x3f62bf35u,0x3f46bf6du,0xbf223f55u,0x3ef1be48u,0x3f7fbf7bu,0x3e95bf0eu,
  0xbe953e48u,0xbf223f0eu,0xbf623f55u,0xbf7f3f7bu,0xbdc90000u,0xbef13ec4u,0xbf463f35u,0xbf753f6du,
  0x3f75bf7bu,0x3f46bf55u,0x3ef1bf0eu,0x3dc9be48u,0x3f7fbf80u,0x3f62bf6du,0x3f22bf35u,0x3e95bec4u,
  0x3e95be48u,0x3f22bf0eu,0x3f62bf55u,0x3f7fbf7bu,0x3dc90000u,0x3ef1bec4u,0x3f46bf35u,0x3f75bf6du,
  0xbf753f7bu,0xbf463f55u,0xbef13f0eu,0xbdc93e48u,0xbf7f3f80u,0xbf623f6du,0xbf223f35u,0xbe953ec4u,
  0xbf7f0000u,0xbf62bec4u,0xbf22bf35u,0xbe95bf6du,0x3f753e48u,0x3f463f0eu,0x3ef13f55u,0x3dc93f7bu,
  0x3dc9bf80u,0x3ef1bf6du,0x3f46bf35u,0x3f75bec4u,0xbe953f7bu,0xbf223f55u,0xbf623f0eu,0xbf7f3e48u,
  0x3f7f0000u,0x3f623ec4u,0x3f223f35u,0x3e953f6du,0xbf75be48u,0xbf46bf0eu,0xbef1bf55u,0xbdc9bf7bu,
  0xbdc93f80u,0xbef13f6du,0xbf463f35u,0xbf753ec4u,0x3e95bf7bu,0x3f22bf55u,0x3f62bf0eu,0x3f7fbe48u,
  0x3f223f0eu,0xbef13f7bu,0xbf7f3e48u,0xbe95bf55u,0xbf750000u,0xbdc9bf6du,0x3f62bf35u,0x3f463ec4u,
  0x3f46bf55u,0x3f623e48u,0xbdc93f7bu,0xbf753f0eu,0xbe953f80u,0xbf7f3ec4u,0xbef1bf35u,0x3f22bf6du,
  0xbf22bf0eu,0x3ef1bf7bu,0x3f7fbe48u,0x3e953f55u,0x3f750000u,0x3dc93f6du,0xbf623f35u,0xbf46bec4u,
  0xbf463f55u,0xbf62be48u,0x3dc9bf7bu,0x3f75bf0eu,0x3e95bf80u,0x3f7fbec4u,0x3ef13f35u,0xbf223f6du,
  0x3ef1bf80u,0x3f223ec4u,0xbf753f35u,0x3dc9bf6du,0xbf7f3f0eu,0x3e95bf7bu,0x3f463e48u,0xbf623f55u,
  0xbf620000u,0x3f46bf6du,0x3e953f35u,0xbf7f3ec4u,0x3dc93f55u,0xbf753e48u,0x3f22bf7bu,0x3ef13f0eu,
  0xbef13f80u,0xbf22bec4u,0x3f75bf35u,0xbdc93f6du,0x3f7fbf0eu,0xbe953f7bu,0xbf46be48u,0x3f62bf55u,
  0x3f620000u,0xbf463f6du,0xbe95bf35u,0x3f7fbec4u,0xbdc9bf55u,0x3f75be48u,0xbf223f7bu,0xbef1bf0eu,
  0x3f62be48u,0xbf7f3f0eu,0x3f75bf55u,0xbf463f7bu,0xbf223f80u,0x3e95bf6du,0x3dc93f35u,0xbef1bec4u,
  0xbef13f7bu,0x3dc9bf55u,0x3e953f0eu,0xbf22be48u,0xbf460000u,0x3f75bec4u,0xbf7f3f35u,0x3f62bf6du,
  0xbf623e48u,0x3f7fbf0eu,0xbf753f55u,0x3f46bf7bu,0x3f22bf80u,0xbe953f6du,0xbdc9bf35u,0x3ef13ec4u,
  0x3ef1bf7bu,0xbdc93f55u,0xbe95bf0eu,0x3f223e48u,0x3f460000u,0xbf753ec4u,0x3f7fbf35u,0xbf623f6du,
  0x3f220000u,0xbe95bec4u,0xbdc93f35u,0x3ef1bf6du,0x3f62bf7bu,0xbf7f3f55u,0x3f75bf0eu,0xbf463e48u,
  0xbf463f80u,0x3f75bf6du,0xbf7f3f35u,0x3f62bec4u,0x3ef13e48u,0xbdc9bf0eu,0xbe953f55u,0x3f22bf7bu,
  0xbf220000u,0x3e953ec4u,0x3dc9bf35u,0xbef13f6du,0xbf623f7bu,0x3f7fbf55u,0xbf753f0eu,0x3f46be48u,
  0x3f46bf80u,0xbf753f6du,0x3f7fbf35u,0xbf623ec4u,0xbef1be48u,0x3dc93f0eu,0x3e95bf55u,0xbf223f7bu,
  0x3f7fbf55u,0xbe95be48u,0xbf463f7bu,0x3f62bf0eu,0x3ef10000u,0x3f22bf6du,0xbf753f35u,0x3dc93ec4u,
  0x3dc9bf0eu,0xbf753f7bu,0x3f22be48u,0x3ef1bf55u,0x3f62bf80u,0xbf463ec4u,0xbe953f35u,0x3f7fbf6du,
  0xbf7f3f55u,0x3e953e48u,0x3f46bf7bu,0xbf623f0eu,0xbef10000u,0xbf223f6du,0x3f75bf35u,0xbdc9bec4u,
  0xbdc93f0eu,0x3f75bf7bu,0xbf223e48u,0xbef13f55u,0xbf623f80u,0x3f46bec4u,0x3e95bf35u,0xbf7f3f6du,
  0xbf753f80u,0xbdc93ec4u,0x3f62bf35u,0x3f46bf6du,0xbf223f55u,0x3ef1be48u,0x3f7fbf7bu,0x3e95bf0eu,
  0x3e950000u,0x3f7fbf6du,0x3ef1bf35u,0xbf223ec4u,0x3f46bf0eu,0x3f62bf7bu,0xbdc9be48u,0xbf753f55u,
  0x3f75bf80u,0x3dc9bec4u,0xbf623f35u,0xbf463f6du,0x3f22bf55u,0xbef13e48u,0xbf7f3f7bu,0xbe953f0eu,
  0xbe950000u,0xbf7f3f6du,0xbef13f35u,0x3f22bec4u,0xbf463f0eu,0xbf623f7bu,0x3dc93e48u,0x3f75bf55u,
  0x3f75bf7bu,0x3f46bf55u,0x3ef1bf0eu,0x3dc9be48u,0x3f7fbf80u,0x3f62bf6du,0x3f22bf35u,0x3e95bec4u,
  0x3e95be48u,0x3f22bf0eu,0x3f62bf55u,0x3f7fbf7bu,0x3dc90000u,0x3ef1bec4u,0x3f46bf35u,0x3f75bf6du,
  0xbf753f7bu,0xbf463f55u,0xbef13f0eu,0xbdc93e48u,0xbf7f3f80u,0xbf623f6du,0xbf223f35u,0xbe953ec4u,
  0xbe953e48u,0xbf223f0eu,0xbf623f55u,0xbf7f3f7bu,0xbdc90000u,0xbef13ec4u,0xbf463f35u,0xbf753f6du,
  0xbf7f3f80u,0xbf623f6du,0xbf223f35u,0xbe953ec4u,0xbf753f7bu,0xbf463f55u,0xbef13f0eu,0xbdc93e48u,
  0x3dc90000u,0x3ef1bec4u,0x3f46bf35u,0x3f75bf6du,0x3e95be48u,0x3f22bf0eu,0x3f62bf55u,0x3f7fbf7bu,
  0x3f7fbf80u,0x3f62bf6du,0x3f22bf35u,0x3e95bec4u,0x3f75bf7bu,0x3f46bf55u,0x3ef1bf0eu,0x3dc9be48u,
  0xbdc90000u,0xbef13ec4u,0xbf463f35u,0xbf753f6du,0xbe953e48u,0xbf223f0eu,0xbf623f55u,0xbf7f3f7bu,
  0xbf223f55u,0x3ef1be48u,0x3f7fbf7bu,0x3e95bf0eu,0xbf753f80u,0xbdc93ec4u,0x3f62bf35u,0x3f46bf6du,
  0xbf463f0eu,0xbf623f7bu,0x3dc93e48u,0x3f75bf55u,0xbe950000u,0xbf7f3f6du,0xbef13f35u,0x3f22bec4u,
  0x3f22bf55u,0xbef13e48u,0xbf7f3f7bu,0xbe953f0eu,0x3f75bf80u,0x3dc9bec4u,0xbf623f35u,0xbf463f6du,
  0x3f46bf0eu,0x3f62bf7bu,0xbdc9be48u,0xbf753f55u,0x3e950000u,0x3f7fbf6du,0x3ef1bf35u,0xbf223ec4u,
  0x3ef10000u,0x3f22bf6du,0xbf753f35u,0x3dc93ec4u,0x3f7fbf55u,0xbe95be48u,0xbf463f7bu,0x3f62bf0eu,
  0xbf623f80u,0x3f46bec4u,0x3e95bf35u,0xbf7f3f6du,0xbdc93f0eu,0x3f75bf7bu,0xbf223e48u,0xbef13f55u,
  0xbef10000u,0xbf223f6du,0x3f75bf35u,0xbdc9bec4u,0xbf7f3f55u,0x3e953e48u,0x3f46bf7bu,0xbf623f0eu,
  0x3f62bf80u,0xbf463ec4u,0xbe953f35u,0x3f7fbf6du,0x3dc9bf0eu,0xbf753f7bu,0x3f22be48u,0x3ef1bf55u,
  0xbf623f7bu,0x3f7fbf55u,0xbf753f0eu,0x3f46be48u,0xbf220000u,0x3e953ec4u,0x3dc9bf35u,0xbef13f6du,
  0x3ef13e48u,0xbdc9bf0eu,0xbe953f55u,0x3f22bf7bu,0xbf463f80u,0x3f75bf6du,0xbf7f3f35u,0x3f62bec4u,
  0x3f62bf7bu,0xbf7f3f55u,0x3f75bf0eu,0xbf463e48u,0x3f220000u,0xbe95bec4u,0xbdc93f35u,0x3ef1bf6du,
  0xbef1be48u,0x3dc93f0eu,0x3e95bf55u,0xbf223f7bu,0x3f46bf80u,0xbf753f6du,0x3f7fbf35u,0xbf623ec4u,
  0x3f22bf80u,0xbe953f6du,0xbdc9bf35u,0x3ef13ec4u,0xbf623e48u,0x3f7fbf0eu,0xbf753f55u,0x3f46bf7bu,
  0xbf460000u,0x3f75bec4u,0xbf7f3f35u,0x3f62bf6du,0xbef13f7bu,0x3dc9bf55u,0x3e953f0eu,0xbf22be48u,
  0xbf223f80u,0x3e95bf6du,0x3dc93f35u,0xbef1bec4u,0x3f62be48u,0xbf7f3f0eu,0x3f75bf55u,0xbf463f7bu,
  0x3f460000u,0xbf753ec4u,0x3f7fbf35u,0xbf623f6du,0x3ef1bf7bu,0xbdc93f55u,0xbe95bf0eu,0x3f223e48u,
  0xbf7f3f0eu,0x3e95bf7bu,0x3f463e48u,0xbf623f55u,0x3ef1bf80u,0x3f223ec4u,0xbf753f35u,0x3dc9bf6du,
  0xbdc9bf55u,0x3f75be48u,0xbf223f7bu,0xbef1bf0eu,0x3f620000u,0xbf463f6du,0xbe95bf35u,0x3f7fbec4u,
  0x3f7fbf0eu,0xbe953f7bu,0xbf46be48u,0x3f62bf55u,0xbef13f80u,0xbf22bec4u,0x3f75bf35u,0xbdc93f6du,
  0x3dc93f55u,0xbf753e48u,0x3f22bf7bu,0x3ef13f0eu,0xbf620000u,0x3f46bf6du,0x3e953f35u,0xbf7f3ec4u,
  0xbf750000u,0xbdc9bf6du,0x3f62bf35u,0x3f463ec4u,0x3f223f0eu,0xbef13f7bu,0xbf7f3e48u,0xbe95bf55u,
  0x3e95bf80u,0x3f7fbec4u,0x3ef13f35u,0xbf223f6du,0xbf463f55u,0xbf62be48u,0x3dc9bf7bu,0x3f75bf0eu,
  0x3f750000u,0x3dc93f6du,0xbf623f35u,0xbf46bec4u,0xbf22bf0eu,0x3ef1bf7bu,0x3f7fbe48u,0x3e953f55u,
  0xbe953f80u,0xbf7f3ec4u,0xbef1bf35u,0x3f22bf6du,0x3f46bf55u,0x3f623e48u,0xbdc93f7bu,0xbf753f0eu,
  0xbf75be48u,0xbf46bf0eu,0xbef1bf55u,0xbdc9bf7bu,0x3f7f0000u,0x3f623ec4u,0x3f223f35u,0x3e953f6du,
  0xbe953f7bu,0xbf223f55u,0xbf623f0eu,0xbf7f3e48u,0x3dc9bf80u,0x3ef1bf6du,0x3f46bf35u,0x3f75bec4u,
  0x3f753e48u,0x3f463f0eu,0x3ef13f55u,0x3dc93f7bu,0xbf7f0000u,0xbf62bec4u,0xbf22bf35u,0xbe95bf6du,
  0x3e95bf7bu,0x3f22bf55u,0x3f62bf0eu,0x3f7fbe48u,0xbdc93f80u,0xbef13f6du,0xbf463f35u,0xbf753ec4u,
  0x3dc90000u,0x3ef1bec4u,0x3f46bf35u,0x3f75bf6du,0x3e95be48u,0x3f22bf0eu,0x3f62bf55u,0x3f7fbf7bu,
  0x3f7fbf80u,0x3f62bf6du,0x3f22bf35u,0x3e95bec4u,0x3f75bf7bu,0x3f46bf55u,0x3ef1bf0eu,0x3dc9be48u,
  0xbdc90000u,0xbef13ec4u,0xbf463f35u,0xbf753f6du,0xbe953e48u,0xbf223f0eu,0xbf623f55u,0xbf7f3f7bu,
  0xbf7f3f80u,0xbf623f6du,0xbf223f35u,0xbe953ec4u,0xbf753f7bu,0xbf463f55u,0xbef13f0eu,0xbdc93e48u,
  0x3f46bf0eu,0x3f62bf7bu,0xbdc9be48u,0xbf753f55u,0x3e950000u,0x3f7fbf6du,0x3ef1bf35u,0xbf223ec4u,
  0xbf223f55u,0x3ef1be48u,0x3f7fbf7bu,0x3e95bf0eu,0xbf753f80u,0xbdc93ec4u,0x3f62bf35u,0x3f46bf6du,
  0xbf463f0eu,0xbf623f7bu,0x3dc93e48u,0x3f75bf55u,0xbe950000u,0xbf7f3f6du,0xbef13f35u,0x3f22bec4u,
  0x3f22bf55u,0xbef13e48u,0xbf7f3f7bu,0xbe953f0eu,0x3f75bf80u,0x3dc9bec4u,0xbf623f35u,0xbf463f6du,
  0x3f62bf80u,0xbf463ec4u,0xbe953f35u,0x3f7fbf6du,0x3dc9bf0eu,0xbf753f7bu,0x3f22be48u,0x3ef1bf55u,
  0x3ef10000u,0x3f22bf6du,0xbf753f35u,0x3dc93ec4u,0x3f7fbf55u,0xbe95be48u,0xbf463f7bu,0x3f62bf0eu,
  0xbf623f80u,0x3f46bec4u,0x3e95bf35u,0xbf7f3f6du,0xbdc93f0eu,0x3f75bf7bu,0xbf223e48u,0xbef13f55u,
  0xbef10000u,0xbf223f6du,0x3f75bf35u,0xbdc9bec4u,0xbf7f3f55u,0x3e953e48u,0x3f46bf7bu,0xbf623f0eu,
  0x3ef13e48u,0xbdc9bf0eu,0xbe953f55u,0x3f22bf7bu,0xbf463f80u,0x3f75bf6du,0xbf7f3f35u,0x3f62bec4u,
  0x3f62bf7bu,0xbf7f3f55u,0x3f75bf0eu,0xbf463e48u,0x3f220000u,0xbe95bec4u,0xbdc93f35u,0x3ef1bf6du,
  0xbef1be48u,0x3dc93f0eu,0x3e95bf55u,0xbf223f7bu,0x3f46bf80u,0xbf753f6du,0x3f7fbf35u,0xbf623ec4u,
  0xbf623f7bu,0x3f7fbf55u,0xbf753f0eu,0x3f46be48u,0xbf220000u,0x3e953ec4u,0x3dc9bf35u,0xbef13f6du,
  0xbf460000u,0x3f75bec4u,0xbf7f3f35u,0x3f62bf6du,0xbef13f7bu,0x3dc9bf55u,0x3e953f0eu,0xbf22be48u,
  0xbf223f80u,0x3e95bf6du,0x3dc93f35u,0xbef1bec4u,0x3f62be48u,0xbf7f3f0eu,0x3f75bf55u,0xbf463f7bu,
  0x3f460000u,0xbf753ec4u,0x3f7fbf35u,0xbf623f6du,0x3ef1bf7bu,0xbdc93f55u,0xbe95bf0eu,0x3f223e48u,
  0x3f22bf80u,0xbe953f6du,0xbdc9bf35u,0x3ef13ec4u,0xbf623e48u,0x3f7fbf0eu,0xbf753f55u,0x3f46bf7bu,
  0x3dc93f55u,0xbf753e48u,0x3f22bf7bu,0x3ef13f0eu,0xbf620000u,0x3f46bf6du,0x3e953f35u,0xbf7f3ec4u,
  0xbf7f3f0eu,0x3e95bf7bu,0x3f463e48u,0xbf623f55u,0x3ef1bf80u,0x3f223ec4u,0xbf753f35u,0x3dc9bf6du,
  0xbdc9bf55u,0x3f75be48u,0xbf223f7bu,0xbef1bf0eu,0x3f620000u,0xbf463f6du,0xbe95bf35u,0x3f7fbec4u,
  0x3f7fbf0eu,0xbe953f7bu,0xbf46be48u,0x3f62bf55u,0xbef13f80u,0xbf22bec4u,0x3f75bf35u,0xbdc93f6du,
  0xbe953f80u,0xbf7f3ec4u,0xbef1bf35u,0x3f22bf6du,0x3f46bf55u,0x3f623e48u,0xbdc93f7bu,0xbf753f0eu,
  0xbf750000u,0xbdc9bf6du,0x3f62bf35u,0x3f463ec4u,0x3f223f0eu,0xbef13f7bu,0xbf7f3e48u,0xbe95bf55u,
  0x3e95bf80u,0x3f7fbec4u,0x3ef13f35u,0xbf223f6du,0xbf463f55u,0xbf62be48u,0x3dc9bf7bu,0x3f75bf0eu,
  0x3f750000u,0x3dc93f6du,0xbf623f35u,0xbf46bec4u,0xbf22bf0eu,0x3ef1bf7bu,0x3f7fbe48u,0x3e953f55u,
  0xbe953f7bu,0xbf223f55u,0xbf623f0eu,0xbf7f3e48u,0x3dc9bf80u,0x3ef1bf6du,0x3f46bf35u,0x3f75bec4u,
  0x3f753e48u,0x3f463f0eu,0x3ef13f55u,0x3dc93f7bu,0xbf7f0000u,0xbf62bec4u,0xbf22bf35u,0xbe95bf6du,
  0x3e95bf7bu,0x3f22bf55u,0x3f62bf0eu,0x3f7fbe48u,0xbdc93f80u,0xbef13f6du,0xbf463f35u,0xbf753ec4u,
  0xbf75be48u,0xbf46bf0eu,0xbef1bf55u,0xbdc9bf7bu,0x3f7f0000u,0x3f623ec4u,0x3f223f35u,0x3e953f6du,
  0x3dc93f80u,0x3ef13f6du,0x3f463f35u,0x3f753ec4u,0xbe95bf7bu,0xbf22bf55u,0xbf62bf0eu,0xbf7fbe48u,
  0x3f7f0000u,0x3f62bec4u,0x3f22bf35u,0x3e95bf6du,0xbf753e48u,0xbf463f0eu,0xbef13f55u,0xbdc93f7bu,
  0xbdc9bf80u,0xbef1bf6du,0xbf46bf35u,0xbf75bec4u,0x3e953f7bu,0x3f223f55u,0x3f623f0eu,0x3f7f3e48u,
  0xbf7f0000u,0xbf623ec4u,0xbf223f35u,0xbe953f6du,0x3f75be48u,0x3f46bf0eu,0x3ef1bf55u,0x3dc9bf7bu,
  0xbf46bf55u,0xbf623e48u,0x3dc93f7bu,0x3f753f0eu,0x3e953f80u,0x3f7f3ec4u,0x3ef1bf35u,0xbf22bf6du,
  0x3f22bf0eu,0xbef1bf7bu,0xbf7fbe48u,0xbe953f55u,0xbf750000u,0xbdc93f6du,0x3f623f35u,0x3f46bec4u,
  0x3f463f55u,0x3f62be48u,0xbdc9bf7bu,0xbf75bf0eu,0xbe95bf80u,0xbf7fbec4u,0xbef13f35u,0x3f223f6du,
  0xbf223f0eu,0x3ef13f7bu,0x3f7f3e48u,0x3e95bf55u,0x3f750000u,0x3dc9bf6du,0xbf62bf35u,0xbf463ec4u,
  0x3f620000u,0xbf46bf6du,0xbe953f35u,0x3f7f3ec4u,0xbdc93f55u,0x3f753e48u,0xbf22bf7bu,0xbef13f0eu,
  0x3ef13f80u,0x3f22bec4u,0xbf75bf35u,0x3dc93f6du,0xbf7fbf0eu,0x3e953f7bu,0x3f46be48u,0xbf62bf55u,
  0xbf620000u,0x3f463f6du,0x3e95bf35u,0xbf7fbec4u,0x3dc9bf55u,0xbf75be48u,0x3f223f7bu,0x3ef1bf0eu,
  0xbef1bf80u,0xbf223ec4u,0x3f753f35u,0xbdc9bf6du,0x3f7f3f0eu,0xbe95bf7bu,0xbf463e48u,0x3f623f55u,
  0xbef1bf7bu,0x3dc93f55u,0x3e95bf0eu,0xbf223e48u,0xbf460000u,0x3f753ec4u,0xbf7fbf35u,0x3f623f6du,
  0xbf62be48u,0x3f7f3f0eu,0xbf75bf55u,0x3f463f7bu,0x3f223f80u,0xbe95bf6du,0xbdc93f35u,0x3ef1bec4u,
  0x3ef13f7bu,0xbdc9bf55u,0xbe953f0eu,0x3f22be48u,0x3f460000u,0xbf75bec4u,0x3f7f3f35u,0xbf62bf6du,
  0x3f623e48u,0xbf7fbf0eu,0x3f753f55u,0xbf46bf7bu,0xbf22bf80u,0x3e953f6du,0x3dc9bf35u,0xbef13ec4u,
  0xbf46bf80u,0x3f753f6du,0xbf7fbf35u,0x3f623ec4u,0x3ef1be48u,0xbdc93f0eu,0xbe95bf55u,0x3f223f7bu,
  0xbf220000u,0x3e95bec4u,0x3dc93f35u,0xbef1bf6du,0xbf62bf7bu,0x3f7f3f55u,0xbf75bf0eu,0x3f463e48u,
  0x3f463f80u,0xbf75bf6du,0x3f7f3f35u,0xbf62bec4u,0xbef13e48u,0x3dc9bf0eu,0x3e953f55u,0xbf22bf7bu,
  0x3f220000u,0xbe953ec4u,0xbdc9bf35u,0x3ef13f6du,0x3f623f7bu,0xbf7fbf55u,0x3f753f0eu,0xbf46be48u,
  0xbdc9bf0eu,0x3f753f7bu,0xbf22be48u,0xbef1bf55u,0xbf62bf80u,0x3f463ec4u,0x3e953f35u,0xbf7fbf6du,
  0x3f7f3f55u,0xbe953e48u,0xbf46bf7bu,0x3f623f0eu,0x3ef10000u,0x3f223f6du,0xbf75bf35u,0x3dc9bec4u,
  0x3dc93f0eu,0xbf75bf7bu,0x3f223e48u,0x3ef13f55u,0x3f623f80u,0xbf46bec4u,0xbe95bf35u,0x3f7f3f6du,
  0xbf7fbf55u,0x3e95be48u,0x3f463f7bu,0xbf62bf0eu,0xbef10000u,0xbf22bf6du,0x3f753f35u,0xbdc93ec4u,
  0xbe950000u,0xbf7fbf6du,0xbef1bf35u,0x3f223ec4u,0xbf46bf0eu,0xbf62bf7bu,0x3dc9be48u,0x3f753f55u,
  0xbf75bf80u,0xbdc9bec4u,0x3f623f35u,0x3f463f6du,0xbf22bf55u,0x3ef13e48u,0x3f7f3f7bu,0x3e953f0eu,
  0x3e950000u,0x3f7f3f6du,0x3ef13f35u,0xbf22bec4u,0x3f463f0eu,0x3f623f7bu,0xbdc93e48u,0xbf75bf55u,
  0x3f753f80u,0x3dc93ec4u,0xbf62bf35u,0xbf46bf6du,0x3f223f55u,0xbef1be48u,0xbf7fbf7bu,0xbe95bf0eu,
  0x3e953e48u,0x3f223f0eu,0x3f623f55u,0x3f7f3f7bu,0x3dc90000u,0x3ef13ec4u,0x3f463f35u,0x3f753f6du,
  0xbf75bf7bu,0xbf46bf55u,0xbef1bf0eu,0xbdc9be48u,0xbf7fbf80u,0xbf62bf6du,0xbf22bf35u,0xbe95bec4u,
  0xbe95be48u,0xbf22bf0eu,0xbf62bf55u,0xbf7fbf7bu,0xbdc90000u,0xbef1bec4u,0xbf46bf35u,0xbf75bf6du,
  0x3f753f7bu,0x3f463f55u,0x3ef13f0eu,0x3dc93e48u,0x3f7f3f80u,0x3f623f6du,0x3f223f35u,0x3e953ec4u,
  0x3f7f0000u,0x3f62bec4u,0x3f22bf35u,0x3e95bf6du,0xbf753e48u,0xbf463f0eu,0xbef13f55u,0xbdc93f7bu,
  0xbdc9bf80u,0xbef1bf6du,0xbf46bf35u,0xbf75bec4u,0x3e953f7bu,0x3f223f55u,0x3f623f0eu,0x3f7f3e48u,
  0xbf7f0000u,0xbf623ec4u,0xbf223f35u,0xbe953f6du,0x3f75be48u,0x3f46bf0eu,0x3ef1bf55u,0x3dc9bf7bu,
  0x3dc93f80u,0x3ef13f6du,0x3f463f35u,0x3f753ec4u,0xbe95bf7bu,0xbf22bf55u,0xbf62bf0eu,0xbf7fbe48u,
  0xbf223f0eu,0x3ef13f7bu,0x3f7f3e48u,0x3e95bf55u,0x3f750000u,0x3dc9bf6du,0xbf62bf35u,0xbf463ec4u,
  0xbf46bf55u,0xbf623e48u,0x3dc93f7bu,0x3f753f0eu,0x3e953f80u,0x3f7f3ec4u,0x3ef1bf35u,0xbf22bf6du,
  0x3f22bf0eu,0xbef1bf7bu,0xbf7fbe48u,0xbe953f55u,0xbf750000u,0xbdc93f6du,0x3f623f35u,0x3f46bec4u,
  0x3f463f55u,0x3f62be48u,0xbdc9bf7bu,0xbf75bf0eu,0xbe95bf80u,0xbf7fbec4u,0xbef13f35u,0x3f223f6du,
  0xbef1bf80u,0xbf223ec4u,0x3f753f35u,0xbdc9bf6du,0x3f7f3f0eu,0xbe95bf7bu,0xbf463e48u,0x3f623f55u,
  0x3f620000u,0xbf46bf6du,0xbe953f35u,0x3f7f3ec4u,0xbdc93f55u,0x3f753e48u,0xbf22bf7bu,0xbef13f0eu,
  0x3ef13f80u,0x3f22bec4u,0xbf75bf35u,0x3dc93f6du,0xbf7fbf0eu,0x3e953f7bu,0x3f46be48u,0xbf62bf55u,
  0xbf620000u,0x3f463f6du,0x3e95bf35u,0xbf7fbec4u,0x3dc9bf55u,0xbf75be48u,0x3f223f7bu,0x3ef1bf0eu,
  0xbf62be48u,0x3f7f3f0eu,0xbf75bf55u,0x3f463f7bu,0x3f223f80u,0xbe95bf6du,0xbdc93f35u,0x3ef1bec4u,
  0x3ef13f7bu,0xbdc9bf55u,0xbe953f0eu,0x3f22be48u,0x3f460000u,0xbf75bec4u,0x3f7f3f35u,0xbf62bf6du,
  0x3f623e48u,0xbf7fbf0eu,0x3f753f55u,0xbf46bf7bu,0xbf22bf80u,0x3e953f6du,0x3dc9bf35u,0xbef13ec4u,
  0xbef1bf7bu,0x3dc93f55u,0x3e95bf0eu,0xbf223e48u,0xbf460000u,0x3f753ec4u,0xbf7fbf35u,0x3f623f6du,
  0xbf220000u,0x3e95bec4u,0x3dc93f35u,0xbef1bf6du,0xbf62bf7bu,0x3f7f3f55u,0xbf75bf0eu,0x3f463e48u,
  0x3f463f80u,0xbf75bf6du,0x3f7f3f35u,0xbf62bec4u,0xbef13e48u,0x3dc9bf0eu,0x3e953f55u,0xbf22bf7bu,
  0x3f220000u,0xbe953ec4u,0xbdc9bf35u,0x3ef13f6du,0x3f623f7bu,0xbf7fbf55u,0x3f753f0eu,0xbf46be48u,
  0xbf46bf80u,0x3f753f6du,0xbf7fbf35u,0x3f623ec4u,0x3ef1be48u,0xbdc93f0eu,0xbe95bf55u,0x3f223f7bu,
  0xbf7fbf55u,0x3e95be48u,0x3f463f7bu,0xbf62bf0eu,0xbef10000u,0xbf22bf6du,0x3f753f35u,0xbdc93ec4u,
  0xbdc9bf0eu,0x3f753f7bu,0xbf22be48u,0xbef1bf55u,0xbf62bf80u,0x3f463ec4u,0x3e953f35u,0xbf7fbf6du,
  0x3f7f3f55u,0xbe953e48u,0xbf46bf7bu,0x3f623f0eu,0x3ef10000u,0x3f223f6du,0xbf75bf35u,0x3dc9bec4u,
  0x3dc93f0eu,0xbf75bf7bu,0x3f223e48u,0x3ef13f55u,0x3f623f80u,0xbf46bec4u,0xbe95bf35u,0x3f7f3f6du,
  0x3f753f80u,0x3dc93ec4u,0xbf62bf35u,0xbf46bf6du,0x3f223f55u,0xbef1be48u,0xbf7fbf7bu,0xbe95bf0eu,
  0xbe950000u,0xbf7fbf6du,0xbef1bf35u,0x3f223ec4u,0xbf46bf0eu,0xbf62bf7bu,0x3dc9be48u,0x3f753f55u,
  0xbf75bf80u,0xbdc9bec4u,0x3f623f35u,0x3f463f6du,0xbf22bf55u,0x3ef13e48u,0x3f7f3f7bu,0x3e953f0eu,
  0x3e950000u,0x3f7f3f6du,0x3ef13f35u,0xbf22bec4u,0x3f463f0eu,0x3f623f7bu,0xbdc93e48u,0xbf75bf55u,
  0xbf75bf7bu,0xbf46bf55u,0xbef1bf0eu,0xbdc9be48u,0xbf7fbf80u,0xbf62bf6du,0xbf22bf35u,0xbe95bec4u,
  0xbe95be48u,0xbf22bf0eu,0xbf62bf55u,0xbf7fbf7bu,0xbdc90000u,0xbef1bec4u,0xbf46bf35u,0xbf75bf6du,
  0x3f753f7bu,0x3f463f55u,0x3ef13f0eu,0x3dc93e48u,0x3f7f3f80u,0x3f623f6du,0x3f223f35u,0x3e953ec4u,
  0x3e953e48u,0x3f223f0eu,0x3f623f55u,0x3f7f3f7bu,0x3dc90000u,0x3ef13ec4u,0x3f463f35u,0x3f753f6du,
};

__device__ __forceinline__ uint32_t smem_u32(const void* p) { return (uint32_t)__cvta_generic_to_shared(p); }
__device__ __forceinline__ void mbar_init(uint32_t bar, uint32_t cnt) {
  asm volatile("mbarrier.init.shared::cta.b64 [%0], %1;" ::"r"(bar), "r"(cnt) : "memory");
}
__device__ __forceinline__ void mbar_expect_tx(uint32_t bar, uint32_t bytes) {
  asm volatile("mbarrier.arrive.expect_tx.shared::cta.b64 _, [%0], %1;" ::"r"(bar), "r"(bytes) : "memory");
}
__device__ __forceinline__ void mbar_arrive(uint32_t bar) {
  asm volatile("mbarrier.arrive.shared::cta.b64 _, [%0];" ::"r"(bar) : "memory");
}
__device__ __forceinline__ void mbar_arrive_remote(uint32_t bar, uint32_t rank) {
  asm volatile(
      "{\n.reg .b32 a;\nmapa.shared::cluster.u32 a, %0, %1;\n"
      "mbarrier.arrive.shared::cluster.b64 _, [a];\n}" ::"r"(bar), "r"(rank) : "memory");
}
__device__ __forceinline__ void mbar_wait(uint32_t bar, uint32_t parity) {
  asm volatile(
      "{\n.reg .pred p;\n.reg .u32 t0, t1;\n"
      "mbarrier.try_wait.parity.shared::cta.b64 p, [%0], %1;\n"
      "@p bra WAIT_DONE;\n"
      "mov.u32 t0, %%clock;\n"
      "WAIT_LOOP:\n"
      "mbarrier.try_wait.parity.shared::cta.b64 p, [%0], %1;\n"
      "@p bra WAIT_DONE;\n"
      "mov.u32 t1, %%clock;\nsub.u32 t1, t1, t0;\nsetp.lt.u32 p, t1, 0x4000000;\n@p bra WAIT_LOOP;\n"
      "WAIT_DONE:\n}" ::"r"(bar), "r"(parity) : "memory");
}
__device__ __forceinline__ void cluster_arrive() { asm volatile("barrier.cluster.arrive.relaxed.aligned;" ::: "memory"); }
__device__ __forceinline__ void cluster_wait() { asm volatile("barrier.cluster.wait.acquire.aligned;" ::: "memory"); }
__device__ __forceinline__ void fence_async_smem() { asm volatile("fence.proxy.async.shared::cta;" ::: "memory"); }
__device__ __forceinline__ void fence_gpu() { asm volatile("fence.acq_rel.gpu;" ::: "memory"); }
template <int ID, int N>
__device__ __forceinline__ void bar_sync() { asm volatile("bar.sync %0, %1;" ::"n"(ID), "n"(N) : "memory"); }
__device__ __forceinline__ void red_add(uint32_t* p, uint32_t v) {
  asm volatile("red.relaxed.gpu.global.add.u32 [%0], %1;" ::"l"(p), "r"(v) : "memory");
}
__device__ __forceinline__ uint32_t ld_relaxed(const uint32_t* p) {
  uint32_t v;
  asm volatile("ld.relaxed.gpu.global.u32 %0, [%1];" : "=r"(v) : "l"(p) : "memory");
  return v;
}
__device__ __forceinline__ void st_relaxed64(uint2* p, uint32_t lo, uint32_t hi) {
  asm volatile("{\n.reg .b64 v;\nmov.b64 v, {%1, %2};\nst.relaxed.gpu.global.b64 [%0], v;\n}" ::"l"(p), "r"(lo), "r"(hi) : "memory");
}
__device__ __forceinline__ uint4 ld_relaxed128(const void* p) {
  uint4 v;
  asm volatile("ld.relaxed.gpu.global.v4.u32 {%0, %1, %2, %3}, [%4];" : "=r"(v.x), "=r"(v.y), "=r"(v.z), "=r"(v.w) : "l"(p) : "memory");
  return v;
}
__device__ __forceinline__ void poll_counter(const uint32_t* p, uint32_t target) {
  uint32_t it = 0;
#pragma unroll 1
  while ((int32_t)(ld_relaxed(p) - target) < 0 && ++it < (1u << 15)) __nanosleep(40);
}
__device__ __forceinline__ uint4 poll_vec(const void* p, uint32_t par) {
  uint4 v = ld_relaxed128(p);
  uint32_t it = 0;
#pragma unroll 1
  while (((v.x ^ par) & 1) && ++it < (1u << 15)) {
    __nanosleep(100);
    v = ld_relaxed128(p);
  }
  return v;
}
template <int N, typename F>
__device__ __forceinline__ void poll_vecs(uint4 (&v)[N], uint32_t par, F addr) {
#pragma unroll
  for (int m = 0; m < N; m++) v[m] = ld_relaxed128(addr(m));
  uint32_t it = 0;
#pragma unroll 1
  for (;;) {
    uint32_t bad = 0;
#pragma unroll
    for (int m = 0; m < N; m++) bad |= ((v[m].x ^ par) & 1) << m;
    if (bad == 0 || ++it >= (1u << 15)) break;
    __nanosleep(60);
#pragma unroll
    for (int m = 0; m < N; m++)
      if (bad & (1u << m)) v[m] = ld_relaxed128(addr(m));
  }
}
__device__ __forceinline__ uint32_t tag_word(uint32_t w, uint32_t par) { return (w & ~1u) | par; }
__device__ __forceinline__ void tma_2d(uint32_t dst, const CUtensorMap* m, uint32_t bar, int c0, int c1) {
  asm volatile(
      "cp.async.bulk.tensor.2d.shared::cluster.global.mbarrier::complete_tx::bytes [%0], [%1, {%3, %4}], [%2];" ::"r"(dst),
      "l"(m), "r"(bar), "r"(c0), "r"(c1) : "memory");
}
__device__ __forceinline__ void tma_2d_mc(uint32_t dst, const CUtensorMap* m, uint32_t bar, int c0, int c1) {
  asm volatile(
      "cp.async.bulk.tensor.2d.shared::cluster.global.mbarrier::complete_tx::bytes.multicast::cluster [%0], [%1, {%3, %4}], [%2], %5;" ::"r"(dst),
      "l"(m), "r"(bar), "r"(c0), "r"(c1), "h"((uint16_t)3) : "memory");
}
__device__ __forceinline__ void tma_3d_mc(uint32_t dst, const CUtensorMap* m, uint32_t bar, int c0, int c1, int c2) {
  asm volatile(
      "cp.async.bulk.tensor.3d.shared::cluster.global.mbarrier::complete_tx::bytes.multicast::cluster [%0], [%1, {%3, %4, %5}], [%2], %6;" ::"r"(dst),
      "l"(m), "r"(bar), "r"(c0), "r"(c1), "r"(c2), "h"((uint16_t)3) : "memory");
}
__device__ __forceinline__ void bulk_g2s(uint32_t dst, const void* src, uint32_t bytes, uint32_t bar) {
  asm volatile("cp.async.bulk.shared::cluster.global.mbarrier::complete_tx::bytes [%0], [%1], %2, [%3];" ::"r"(dst),
               "l"(src), "r"(bytes), "r"(bar) : "memory");
}
__device__ __forceinline__ void bulk_prefetch_l2(const void* src, uint32_t bytes) {
  asm volatile("cp.async.bulk.prefetch.L2.global [%0], %1;" ::"l"(src), "r"(bytes) : "memory");
}
__device__ __forceinline__ void sts16(uint32_t a, uint32_t v) { asm volatile("st.shared.b16 [%0], %1;" ::"r"(a), "h"((uint16_t)v) : "memory"); }
__device__ __forceinline__ void sts32(uint32_t a, uint32_t v) { asm volatile("st.shared.b32 [%0], %1;" ::"r"(a), "r"(v) : "memory"); }
__device__ __forceinline__ void sts128(uint32_t a, uint4 v) {
  asm volatile("st.shared.v4.b32 [%0], {%1, %2, %3, %4};" ::"r"(a), "r"(v.x), "r"(v.y), "r"(v.z), "r"(v.w) : "memory");
}
__device__ __forceinline__ uint4 lds128(uint32_t a) {
  uint4 v;
  asm volatile("ld.shared.v4.b32 {%0, %1, %2, %3}, [%4];" : "=r"(v.x), "=r"(v.y), "=r"(v.z), "=r"(v.w) : "r"(a) : "memory");
  return v;
}
__device__ __forceinline__ float2 lds64f(uint32_t a) {
  float2 v;
  asm volatile("ld.shared.v2.f32 {%0, %1}, [%2];" : "=f"(v.x), "=f"(v.y) : "r"(a) : "memory");
  return v;
}
__device__ __forceinline__ void stg128(void* p, uint4 v) {
  asm volatile("st.global.v4.b32 [%0], {%1, %2, %3, %4};" ::"l"(p), "r"(v.x), "r"(v.y), "r"(v.z), "r"(v.w) : "memory");
}
__device__ __forceinline__ void wgmma_fence() { asm volatile("wgmma.fence.sync.aligned;" ::: "memory"); }
__device__ __forceinline__ void wgmma_commit() { asm volatile("wgmma.commit_group.sync.aligned;" ::: "memory"); }
template <int N>
__device__ __forceinline__ void wgmma_wait() { asm volatile("wgmma.wait_group.sync.aligned %0;" ::"n"(N) : "memory"); }
template <int N>
__device__ __forceinline__ void reg_fence(float (&d)[N]) {
#pragma unroll
  for (int i = 0; i < N; i++) asm volatile("" : "+f"(d[i])::"memory");
}
__device__ __forceinline__ bool elect_one() {
  uint32_t ok;
  asm volatile("{\n.reg .pred p;\nelect.sync _|p, 0xffffffff;\nselp.u32 %0, 1, 0, p;\n}" : "=r"(ok));
  return ok;
}
__device__ __forceinline__ uint64_t desc_at(uint32_t base16, uint32_t off, uint32_t lbo, uint32_t sbo, uint32_t swz) {
  uint64_t d;
  const uint32_t lo = base16 + (off >> 4) + ((lbo >> 4) << 16), hi = (sbo >> 4) | (swz << 30);
  asm("mov.b64 %0, {%1, %2};" : "=l"(d) : "r"(lo), "r"(hi));
  return d;
}
__device__ __forceinline__ void wgmma_ss_n192_tb1(float (&d)[96], uint64_t da, uint64_t db, int sd) {
  asm volatile("{\n.reg .pred p;\nsetp.ne.b32 p, %98, 0;\n"
    "wgmma.mma_async.sync.aligned.m64n192k16.f32.bf16.bf16 {%0, %1, %2, %3, %4, %5, %6, %7, %8, %9, %10, %11, %12, %13, %14, %15, %16, %17, %18, %19, %20, %21, %22, %23, %24, %25, %26, %27, %28, %29, %30, %31, %32, %33, %34, %35, %36, %37, %38, %39, %40, %41, %42, %43, %44, %45, %46, %47, %48, %49, %50, %51, %52, %53, %54, %55, %56, %57, %58, %59, %60, %61, %62, %63, %64, %65, %66, %67, %68, %69, %70, %71, %72, %73, %74, %75, %76, %77, %78, %79, %80, %81, %82, %83, %84, %85, %86, %87, %88, %89, %90, %91, %92, %93, %94, %95}, %96, %97, p, 1, 1, 0, 1;\n}\n"
    : "+f"(d[0]), "+f"(d[1]), "+f"(d[2]), "+f"(d[3]), "+f"(d[4]), "+f"(d[5]), "+f"(d[6]), "+f"(d[7]), "+f"(d[8]), "+f"(d[9]), "+f"(d[10]), "+f"(d[11]), "+f"(d[12]), "+f"(d[13]), "+f"(d[14]), "+f"(d[15]), "+f"(d[16]), "+f"(d[17]), "+f"(d[18]), "+f"(d[19]), "+f"(d[20]), "+f"(d[21]), "+f"(d[22]), "+f"(d[23]), "+f"(d[24]), "+f"(d[25]), "+f"(d[26]), "+f"(d[27]), "+f"(d[28]), "+f"(d[29]), "+f"(d[30]), "+f"(d[31]), "+f"(d[32]), "+f"(d[33]), "+f"(d[34]), "+f"(d[35]), "+f"(d[36]), "+f"(d[37]), "+f"(d[38]), "+f"(d[39]), "+f"(d[40]), "+f"(d[41]), "+f"(d[42]), "+f"(d[43]), "+f"(d[44]), "+f"(d[45]), "+f"(d[46]), "+f"(d[47]), "+f"(d[48]), "+f"(d[49]), "+f"(d[50]), "+f"(d[51]), "+f"(d[52]), "+f"(d[53]), "+f"(d[54]), "+f"(d[55]), "+f"(d[56]), "+f"(d[57]), "+f"(d[58]), "+f"(d[59]), "+f"(d[60]), "+f"(d[61]), "+f"(d[62]), "+f"(d[63]), "+f"(d[64]), "+f"(d[65]), "+f"(d[66]), "+f"(d[67]), "+f"(d[68]), "+f"(d[69]), "+f"(d[70]), "+f"(d[71]), "+f"(d[72]), "+f"(d[73]), "+f"(d[74]), "+f"(d[75]), "+f"(d[76]), "+f"(d[77]), "+f"(d[78]), "+f"(d[79]), "+f"(d[80]), "+f"(d[81]), "+f"(d[82]), "+f"(d[83]), "+f"(d[84]), "+f"(d[85]), "+f"(d[86]), "+f"(d[87]), "+f"(d[88]), "+f"(d[89]), "+f"(d[90]), "+f"(d[91]), "+f"(d[92]), "+f"(d[93]), "+f"(d[94]), "+f"(d[95])
    : "l"(da), "l"(db), "r"(sd));
}
__device__ __forceinline__ void wgmma_ss_n128_tb0(float (&d)[64], uint64_t da, uint64_t db, int sd) {
  asm volatile("{\n.reg .pred p;\nsetp.ne.b32 p, %66, 0;\n"
    "wgmma.mma_async.sync.aligned.m64n128k16.f32.bf16.bf16 {%0, %1, %2, %3, %4, %5, %6, %7, %8, %9, %10, %11, %12, %13, %14, %15, %16, %17, %18, %19, %20, %21, %22, %23, %24, %25, %26, %27, %28, %29, %30, %31, %32, %33, %34, %35, %36, %37, %38, %39, %40, %41, %42, %43, %44, %45, %46, %47, %48, %49, %50, %51, %52, %53, %54, %55, %56, %57, %58, %59, %60, %61, %62, %63}, %64, %65, p, 1, 1, 0, 0;\n}\n"
    : "+f"(d[0]), "+f"(d[1]), "+f"(d[2]), "+f"(d[3]), "+f"(d[4]), "+f"(d[5]), "+f"(d[6]), "+f"(d[7]), "+f"(d[8]), "+f"(d[9]), "+f"(d[10]), "+f"(d[11]), "+f"(d[12]), "+f"(d[13]), "+f"(d[14]), "+f"(d[15]), "+f"(d[16]), "+f"(d[17]), "+f"(d[18]), "+f"(d[19]), "+f"(d[20]), "+f"(d[21]), "+f"(d[22]), "+f"(d[23]), "+f"(d[24]), "+f"(d[25]), "+f"(d[26]), "+f"(d[27]), "+f"(d[28]), "+f"(d[29]), "+f"(d[30]), "+f"(d[31]), "+f"(d[32]), "+f"(d[33]), "+f"(d[34]), "+f"(d[35]), "+f"(d[36]), "+f"(d[37]), "+f"(d[38]), "+f"(d[39]), "+f"(d[40]), "+f"(d[41]), "+f"(d[42]), "+f"(d[43]), "+f"(d[44]), "+f"(d[45]), "+f"(d[46]), "+f"(d[47]), "+f"(d[48]), "+f"(d[49]), "+f"(d[50]), "+f"(d[51]), "+f"(d[52]), "+f"(d[53]), "+f"(d[54]), "+f"(d[55]), "+f"(d[56]), "+f"(d[57]), "+f"(d[58]), "+f"(d[59]), "+f"(d[60]), "+f"(d[61]), "+f"(d[62]), "+f"(d[63])
    : "l"(da), "l"(db), "r"(sd));
}
__device__ __forceinline__ void wgmma_ss_n128_tb1(float (&d)[64], uint64_t da, uint64_t db, int sd) {
  asm volatile("{\n.reg .pred p;\nsetp.ne.b32 p, %66, 0;\n"
    "wgmma.mma_async.sync.aligned.m64n128k16.f32.bf16.bf16 {%0, %1, %2, %3, %4, %5, %6, %7, %8, %9, %10, %11, %12, %13, %14, %15, %16, %17, %18, %19, %20, %21, %22, %23, %24, %25, %26, %27, %28, %29, %30, %31, %32, %33, %34, %35, %36, %37, %38, %39, %40, %41, %42, %43, %44, %45, %46, %47, %48, %49, %50, %51, %52, %53, %54, %55, %56, %57, %58, %59, %60, %61, %62, %63}, %64, %65, p, 1, 1, 0, 1;\n}\n"
    : "+f"(d[0]), "+f"(d[1]), "+f"(d[2]), "+f"(d[3]), "+f"(d[4]), "+f"(d[5]), "+f"(d[6]), "+f"(d[7]), "+f"(d[8]), "+f"(d[9]), "+f"(d[10]), "+f"(d[11]), "+f"(d[12]), "+f"(d[13]), "+f"(d[14]), "+f"(d[15]), "+f"(d[16]), "+f"(d[17]), "+f"(d[18]), "+f"(d[19]), "+f"(d[20]), "+f"(d[21]), "+f"(d[22]), "+f"(d[23]), "+f"(d[24]), "+f"(d[25]), "+f"(d[26]), "+f"(d[27]), "+f"(d[28]), "+f"(d[29]), "+f"(d[30]), "+f"(d[31]), "+f"(d[32]), "+f"(d[33]), "+f"(d[34]), "+f"(d[35]), "+f"(d[36]), "+f"(d[37]), "+f"(d[38]), "+f"(d[39]), "+f"(d[40]), "+f"(d[41]), "+f"(d[42]), "+f"(d[43]), "+f"(d[44]), "+f"(d[45]), "+f"(d[46]), "+f"(d[47]), "+f"(d[48]), "+f"(d[49]), "+f"(d[50]), "+f"(d[51]), "+f"(d[52]), "+f"(d[53]), "+f"(d[54]), "+f"(d[55]), "+f"(d[56]), "+f"(d[57]), "+f"(d[58]), "+f"(d[59]), "+f"(d[60]), "+f"(d[61]), "+f"(d[62]), "+f"(d[63])
    : "l"(da), "l"(db), "r"(sd));
}
__device__ __forceinline__ void wgmma_rs_n128_tb0(float (&d)[64], uint32_t a0, uint32_t a1, uint32_t a2, uint32_t a3, uint64_t db, int sd) {
  asm volatile("{\n.reg .pred p;\nsetp.ne.b32 p, %69, 0;\n"
    "wgmma.mma_async.sync.aligned.m64n128k16.f32.bf16.bf16 {%0, %1, %2, %3, %4, %5, %6, %7, %8, %9, %10, %11, %12, %13, %14, %15, %16, %17, %18, %19, %20, %21, %22, %23, %24, %25, %26, %27, %28, %29, %30, %31, %32, %33, %34, %35, %36, %37, %38, %39, %40, %41, %42, %43, %44, %45, %46, %47, %48, %49, %50, %51, %52, %53, %54, %55, %56, %57, %58, %59, %60, %61, %62, %63}, {%64, %65, %66, %67}, %68, p, 1, 1, 0;\n}\n"
    : "+f"(d[0]), "+f"(d[1]), "+f"(d[2]), "+f"(d[3]), "+f"(d[4]), "+f"(d[5]), "+f"(d[6]), "+f"(d[7]), "+f"(d[8]), "+f"(d[9]), "+f"(d[10]), "+f"(d[11]), "+f"(d[12]), "+f"(d[13]), "+f"(d[14]), "+f"(d[15]), "+f"(d[16]), "+f"(d[17]), "+f"(d[18]), "+f"(d[19]), "+f"(d[20]), "+f"(d[21]), "+f"(d[22]), "+f"(d[23]), "+f"(d[24]), "+f"(d[25]), "+f"(d[26]), "+f"(d[27]), "+f"(d[28]), "+f"(d[29]), "+f"(d[30]), "+f"(d[31]), "+f"(d[32]), "+f"(d[33]), "+f"(d[34]), "+f"(d[35]), "+f"(d[36]), "+f"(d[37]), "+f"(d[38]), "+f"(d[39]), "+f"(d[40]), "+f"(d[41]), "+f"(d[42]), "+f"(d[43]), "+f"(d[44]), "+f"(d[45]), "+f"(d[46]), "+f"(d[47]), "+f"(d[48]), "+f"(d[49]), "+f"(d[50]), "+f"(d[51]), "+f"(d[52]), "+f"(d[53]), "+f"(d[54]), "+f"(d[55]), "+f"(d[56]), "+f"(d[57]), "+f"(d[58]), "+f"(d[59]), "+f"(d[60]), "+f"(d[61]), "+f"(d[62]), "+f"(d[63])
    : "r"(a0), "r"(a1), "r"(a2), "r"(a3), "l"(db), "r"(sd));
}
__device__ __forceinline__ void wgmma_rs_n64_tb1(float (&d)[32], uint32_t a0, uint32_t a1, uint32_t a2, uint32_t a3, uint64_t db, int sd) {
  asm volatile("{\n.reg .pred p;\nsetp.ne.b32 p, %37, 0;\n"
    "wgmma.mma_async.sync.aligned.m64n64k16.f32.bf16.bf16 {%0, %1, %2, %3, %4, %5, %6, %7, %8, %9, %10, %11, %12, %13, %14, %15, %16, %17, %18, %19, %20, %21, %22, %23, %24, %25, %26, %27, %28, %29, %30, %31}, {%32, %33, %34, %35}, %36, p, 1, 1, 1;\n}\n"
    : "+f"(d[0]), "+f"(d[1]), "+f"(d[2]), "+f"(d[3]), "+f"(d[4]), "+f"(d[5]), "+f"(d[6]), "+f"(d[7]), "+f"(d[8]), "+f"(d[9]), "+f"(d[10]), "+f"(d[11]), "+f"(d[12]), "+f"(d[13]), "+f"(d[14]), "+f"(d[15]), "+f"(d[16]), "+f"(d[17]), "+f"(d[18]), "+f"(d[19]), "+f"(d[20]), "+f"(d[21]), "+f"(d[22]), "+f"(d[23]), "+f"(d[24]), "+f"(d[25]), "+f"(d[26]), "+f"(d[27]), "+f"(d[28]), "+f"(d[29]), "+f"(d[30]), "+f"(d[31])
    : "r"(a0), "r"(a1), "r"(a2), "r"(a3), "l"(db), "r"(sd));
}

__device__ __forceinline__ uint32_t pack_bf16(float lo, float hi) {
  uint32_t r;
  asm("cvt.rn.bf16x2.f32 %0, %1, %2;" : "=r"(r) : "f"(hi), "f"(lo));
  return r;
}
__device__ __forceinline__ float bf_lo(uint32_t v) { return __uint_as_float(v << 16); }
__device__ __forceinline__ float bf_hi(uint32_t v) { return __uint_as_float(v & 0xffff0000u); }
__device__ __forceinline__ float bf_round(float x) { return bf_lo(pack_bf16(x, 0.f)); }
__device__ __forceinline__ uint32_t hmul_bf16x2(uint32_t a, uint32_t b) {
  uint32_t r;
  asm("mul.rn.bf16x2 %0, %1, %2;" : "=r"(r) : "r"(a), "r"(b));
  return r;
}
__device__ __forceinline__ uint32_t hadd_bf16x2(uint32_t a, uint32_t b) {
  uint32_t r;
  asm("add.rn.bf16x2 %0, %1, %2;" : "=r"(r) : "r"(a), "r"(b));
  return r;
}
__device__ __forceinline__ uint32_t hsub_bf16x2(uint32_t a, uint32_t b) {
  uint32_t r;
  asm("sub.rn.bf16x2 %0, %1, %2;" : "=r"(r) : "r"(a), "r"(b));
  return r;
}
__device__ __forceinline__ float silu_f(float g) {
  float e, r;
  asm("ex2.approx.ftz.f32 %0, %1;" : "=f"(e) : "f"(g * -1.4426950408889634f));
  asm("rcp.approx.ftz.f32 %0, %1;" : "=f"(r) : "f"(1.0f + e));
  return g * r;
}
template <int PERIOD>
__device__ __forceinline__ void unit_root(int n, float& cs, float& sn) {
  n %= PERIOD;
  if (n >= PERIOD / 2) n -= PERIOD;
  const float a = (float)n * (6.283185307179586f / PERIOD);
  cs = __cosf(a);
  sn = __sinf(a);
}
__device__ __forceinline__ int phi(int p) { return (p & 0x31) | ((p & 6) << 1) | ((p & 8) >> 2); }
__device__ __forceinline__ int phi_inv(int k) { return (k & 0x31) | ((k & 0xC) >> 1) | ((k & 2) << 2); }

constexpr float C1 = 0.62348980185873353f, C2 = -0.22252093395631440f, C3 = -0.90096886790241913f;
constexpr float S1 = 0.78183148246802981f, S2 = 0.97492791218182361f, S3 = 0.43388373911755812f;

struct Params {
  const __nv_bfloat16* x;
  const uint16_t* wr;
  const uint16_t* wi;
  const __nv_bfloat16* wg;
  const __nv_bfloat16* wu;
  const __nv_bfloat16* wd;
  __nv_bfloat16* out;
};

struct RowStat { float m, a, b; };
__device__ __forceinline__ float swiglu1(float ag, float au, float cg, float cu, const RowStat& st) {
  const float tg = fmaf(-st.m, cg, ag), tu = fmaf(-st.m, cu, au);
  float t;
  asm("tanh.approx.f32 %0, %1;" : "=f"(t) : "f"(tg * st.a));
  return (tg * tu) * fmaf(t, st.b, st.b);
}
template <int GO, int UO, int HO, int NACC>
__device__ __forceinline__ void swiglu_atom(const float (&acc)[NACC], uint32_t (&h)[56], uint32_t cs, const RowStat& st0, const RowStat& st1) {
#pragma unroll
  for (int j = 0; j < 4; j++) {
    const float2 cg = lds64f(cs + j * 32);
    const float2 cu = lds64f(cs + 224 * 4 + j * 32);
    const int a = GO + 4 * j, u = UO + 4 * j;
    h[HO + 2 * j + 0] = pack_bf16(swiglu1(acc[a + 0], acc[u + 0], cg.x, cu.x, st0), swiglu1(acc[a + 1], acc[u + 1], cg.y, cu.y, st0));
    h[HO + 2 * j + 1] = pack_bf16(swiglu1(acc[a + 2], acc[u + 2], cg.x, cu.x, st1), swiglu1(acc[a + 3], acc[u + 3], cg.y, cu.y, st1));
  }
}

struct Ring {
  uint32_t slot = 0, phase = 0;
  __device__ __forceinline__ void advance() {
    if (++slot == kStages) { slot = 0; phase ^= 1; }
  }
};

__global__ void __cluster_dims__(2, 1, 1) __launch_bounds__(512, 1)
fused_gfnet_ffn_kernel(const __grid_constant__ CUtensorMap tmX, const __grid_constant__ CUtensorMap tmG3,
                       const __grid_constant__ CUtensorMap tmU3, const __grid_constant__ CUtensorMap tmG2,
                       const __grid_constant__ CUtensorMap tmU2, const __grid_constant__ CUtensorMap tmD,
                       const __grid_constant__ CUtensorMap tmWR, const __grid_constant__ CUtensorMap tmWI,
                       const __grid_constant__ CUtensorMap tmCG, const __grid_constant__ CUtensorMap tmCU,
                       const Params p) {
  extern __shared__ __align__(1024) uint8_t smem[];
  const uint32_t sb = smem_u32(smem);
  const int tid = threadIdx.x, warp = tid >> 5, lane = tid & 31;
  uint32_t rank;
  asm("mov.u32 %0, %%cluster_ctarank;" : "=r"(rank));
  const int cl = blockIdx.x >> 1;
  const int jF = cl & 7;
  const int iB = (cl >> 3) * 2 + (int)rank;
  const int tF = iB * 8 + jF;

  const int row0 = iB * 128;
  uint32_t epoch0 = 0;
  if (tid == 416) epoch0 = ld_relaxed(&g_cnt[0]);
  const bool el = elect_one();
  if (el) {
    mbar_init(sb + SM_BAR + warp * 8, (unsigned)(warp - 5) < 5u ? 4 : 1);
    if (warp + 16 < kNumBars) mbar_init(sb + SM_BAR + (warp + 16) * 8, warp + 16 == 23 ? 4 : 1);
    asm volatile("fence.mbarrier_init.release.cluster;" ::: "memory");
    if (warp >= 4 && warp < 14) asm volatile("prefetch.tensormap [%0];" ::"l"(&tmX + (warp - 4)) : "memory");
  }
  __syncthreads();
  cluster_arrive();
  if (el && warp == 0) {
    TL2(3, 20);
    mbar_expect_tx(sb + BAR_R, 16 * kD * 2);
    bulk_g2s(sb + SM_FD, p.x + (size_t)tF * 16 * kD, 16 * kD * 2, sb + BAR_R);
    mbar_expect_tx(sb + BAR_X, 16384);
    tma_2d(sb + SM_X, &tmX, sb + BAR_X, 0, row0);
    TL2(3, 21);
  }
  cluster_wait();
  if (el && warp == 1) {
    TL2(3, 23);
    const CUtensorMap* m3 = rank ? &tmU3 : &tmG3;
#pragma unroll
    for (int ks = 0; ks < kStages; ks++) {
      mbar_expect_tx(sb + BAR_FULL + ks * 8, 12288);
      tma_3d_mc(sb + SM_RING + ks * 16384 + rank * 6144, m3, sb + BAR_FULL + ks * 8, 0, ks * 32, jF * 7);
      if (ks == 1 || ks == 3) {
        const int xb = (ks + 1) / 2;
        mbar_expect_tx(sb + BAR_X + xb * 8, 16384);
        tma_2d(sb + SM_X + xb * 16384, &tmX, sb + BAR_X + xb * 8, xb * 64, row0);
      }
      if (ks == 2) {
        mbar_expect_tx(sb + BAR_T, 16384);
        bulk_g2s(sb + SM_T16, g_T16, 16384, sb + BAR_T);
      }
      if (ks == 3) {
        mbar_expect_tx(sb + BAR_C, 14336);
        tma_2d(sb + SM_X + 4 * 16384, (iB & 2) ? &tmCU : &tmCG, sb + BAR_C, jF * 224 + (iB >> 2) * 32, (iB & 1) * 224);
      }
    }
    mbar_expect_tx(sb + BAR_X + 3 * 8, 16384);
    tma_2d(sb + SM_X + 3 * 16384, &tmX, sb + BAR_X + 3 * 8, 3 * 64, row0);
    TL2(3, 24);
  }
  if (tid == 32) TLG(63);

  const int wgi = tid >> 7;
  if (wgi == 3) {
    asm volatile("setmaxnreg.dec.sync.aligned.u32 48;");
    if (warp == 12) {
      if (el) {
        TL(0);
        Ring rg;
        rg.phase = 1;
        {
          const CUtensorMap* m3 = rank ? &tmU3 : &tmG3;
#pragma unroll 1
          for (int ks = kStages; ks < 14; ks++) {
            if (ks == 6 || ks == 8) {
              const int xb = 5 + ((ks - 6) >> 1);
              mbar_expect_tx(sb + BAR_X + xb * 8, 16384);
              tma_2d(sb + SM_X + xb * 16384, &tmX, sb + BAR_X + xb * 8, xb * 64, row0);
            }
            if (ks == 10) {
              const uint32_t dst = sb + SM_RING + rg.slot * 16384;
              mbar_wait(sb + BAR_EMPTY + rg.slot * 8, rg.phase ^ 1);
              mbar_arrive(sb + BAR_FULL + rg.slot * 8);
              mbar_expect_tx(sb + BAR_WT, 2 * 16 * 464);
              tma_2d(dst, &tmWR, sb + BAR_WT, ((tF >> 2) * kCols) & ~7, (tF & 3) * 16);
              tma_2d(dst + 16 * 464, &tmWI, sb + BAR_WT, ((tF >> 2) * kCols) & ~7, (tF & 3) * 16);
              rg.advance();
            }
            const uint32_t full = sb + BAR_FULL + rg.slot * 8;
            mbar_wait(sb + BAR_EMPTY + rg.slot * 8, rg.phase ^ 1);
            TL2(0, ks);
            mbar_expect_tx(full, 12288);
            tma_3d_mc(sb + SM_RING + rg.slot * 16384 + rank * 6144, m3, full, 0, ks * 32, jF * 7);
            rg.advance();
          }
        }
        {
          const CUtensorMap* m2 = rank ? &tmU2 : &tmG2;
#pragma unroll 1
          for (int ps = 0; ps < 2; ps++) {
#pragma unroll 1
            for (int ks = 0; ks < 7; ks++) {
              if (ps == 0 && ks == 1) {
                mbar_wait(sb + BAR_EMPTY + rg.slot * 8, rg.phase ^ 1);
                mbar_arrive(sb + BAR_FULL + rg.slot * 8);
                if (iB < 12) {
                  const int id = iB + 16;
                  mbar_expect_tx(sb + BAR_CD, 14336);
                  tma_2d(sb + SM_RING + rg.slot * 16384, (id & 2) ? &tmCU : &tmCG, sb + BAR_CD, jF * 224 + (id >> 2) * 32, (id & 1) * 224);
                } else {
                  mbar_arrive(sb + BAR_CD);
                }
                rg.advance();
              }
              const uint32_t full = sb + BAR_FULL + rg.slot * 8;
              mbar_wait(sb + BAR_EMPTY + rg.slot * 8, rg.phase ^ 1);
              TL2(0, 14 + ps * 7 + ks);
              mbar_expect_tx(full, 16384);
              tma_3d_mc(sb + SM_RING + rg.slot * 16384 + rank * 8192, m2, full, 0, ks * 64, jF * 7 + 3 + 2 * ps);
              rg.advance();
            }
          }
        }
        TL(2);
        const int f0 = jF * 224 + rank * 64;
#pragma unroll 1
        for (int ld = 0; ld < 14; ld++) {
          const int ps = ld >> 1, st = ld & 1;
          uint32_t full, dst;
          if (ld >= 5 && ld < 12) {
            if (ld == 5) mbar_wait(sb + BAR_XF, 0);
            full = sb + BAR_X + (ld - 5) * 8;
            dst = sb + SM_X + (ld - 5) * 16384;
          } else {
            full = sb + BAR_FULL + rg.slot * 8;
            dst = sb + SM_RING + rg.slot * 16384;
            mbar_wait(sb + BAR_EMPTY + rg.slot * 8, rg.phase ^ 1);
            rg.advance();
          }
          TL2(0, 28 + ld);
          mbar_expect_tx(full, st ? 12288 : 16384);
          tma_2d_mc(dst + rank * 8192, &tmD, full, ps * 64, f0 + st * 128);
          if (st == 0 || rank == 0) tma_2d_mc(dst + rank * 8192 + 4096, &tmD, full, ps * 64, f0 + st * 128 + 32);
        }
      }
    } else if (warp == 13) {
      const uint32_t epoch = epoch0;
      if (lane == 0) {
        *reinterpret_cast<volatile uint32_t*>(smem + SM_EPOCH) = epoch;
        mbar_arrive(sb + BAR_E);
      }
      const uint32_t tag = __shfl_sync(0xffffffffu, epoch, 0) + 1;
      {
        const uint2* st = &g_stats[iB * 128 + 2 * lane];
        uint32_t it = 0;
        uint4 v0, v1;
        do {
          if (it) __nanosleep(250);
          v0 = ld_relaxed128(st);
          v1 = ld_relaxed128(st + 64);
        } while (!__all_sync(0xffffffffu, ((v0.x ^ tag) | (v0.z ^ tag) | (v1.x ^ tag) | (v1.z ^ tag)) << 16 == 0) && ++it < (1u << 15));
        sts128(sb + SM_STATS + lane * 16, make_uint4(v0.x & 0xffff0000u, v0.y, v0.z & 0xffff0000u, v0.w));
        sts128(sb + SM_STATS + 512 + lane * 16, make_uint4(v1.x & 0xffff0000u, v1.y, v1.z & 0xffff0000u, v1.w));
        if (lane == 0) TL(5);
      }
#pragma unroll 1
      for (int ph = 0; ph < 3; ph++) {
        const int c0 = ph ? 32 + 64 * ph : 0, n2 = ph ? 32 : 48;
        uint4 v[3], v2[3];
        uint32_t it = 0, bad;
#pragma unroll 1
        do {
          if (it) __nanosleep(200);
          bad = 0;
#pragma unroll
          for (int u = 0; u < 3; u++) {
            const int c = min(lane + 32 * u, 2 * n2 - 1), mat = c >= n2;
            const uint2* src = &g_csum[mat * kF + jF * 224 + c0 + 2 * (c - mat * n2)];
            v[u] = ld_relaxed128(src);
            v2[u] = ld_relaxed128(src + 2 * kF);
          }
#pragma unroll
          for (int u = 0; u < 3; u++) bad |= (v[u].y ^ tag) | (v[u].w ^ tag) | (v2[u].y ^ tag) | (v2[u].w ^ tag);
        } while (__any_sync(0xffffffffu, bad != 0) && ++it < (1u << 15));
#pragma unroll
        for (int u = 0; u < 3; u++) {
          const int c = min(lane + 32 * u, 2 * n2 - 1), mat = c >= n2;
          asm volatile("st.shared.v2.f32 [%0], {%1, %2};" ::"r"(sb + SM_CS + (mat * 224 + c0 + 2 * (c - mat * n2)) * 4),
                       "f"(__uint_as_float(v[u].x) + __uint_as_float(v2[u].x)), "f"(__uint_as_float(v[u].z) + __uint_as_float(v2[u].z)) : "memory");
        }
        __syncwarp();
        if (lane == 0) { mbar_arrive(ph ? sb + BAR_S1 - 8 + ph * 8 : sb + BAR_S); TL(6 + ph); }
      }
    } else {
      const int hw = warp - 14;
      constexpr uint32_t kSlotC2 = 16 % kStages;
      uint32_t peer_empty;
      asm("mapa.shared::cluster.u32 %0, %1, %2;" : "=r"(peer_empty) : "r"(sb + BAR_EMPTY + kSlotC2 * 8), "r"(rank ^ 1));
#pragma unroll 1
      for (int job = 0; job < 2; job++) {
        const int id = iB + 16 * job;
        mbar_wait(job ? sb + BAR_CD : sb + BAR_C, 0);
        if (tid == 448) TL2(3, 26 + job);
        const uint32_t src = (job ? sb + SM_RING + kSlotC2 * 16384 : sb + SM_X + 4 * 16384) + hw * 32 + (lane & 1) * 16 + (lane >> 1) * 64;
        float a[8];
#pragma unroll
        for (int e = 0; e < 8; e++) a[e] = 0.f;
#pragma unroll 1
        for (int it = 0; it < 2; it++) {
          uint4 c[7];
#pragma unroll
          for (int u = 0; u < 7; u++) c[u] = lds128(src + (it * 7 + u) * 1024);
          if (it == 1) {
#pragma unroll
            for (int u = 0; u < 7; u++) asm volatile("mov.b32 %0, %0;" : "+r"(c[u].x));
            if (job == 0) {
              bar_sync<2, 64>();
              if (warp == 14 && el) {
                mbar_expect_tx(sb + BAR_X + 4 * 8, 16384);
                tma_2d(sb + SM_X + 4 * 16384, &tmX, sb + BAR_X + 4 * 8, 4 * 64, row0);
              }
            } else {
              __syncwarp();
              if (lane == 0) {
                mbar_arrive(sb + BAR_EMPTY + kSlotC2 * 8);
                asm volatile("mbarrier.arrive.shared::cluster.b64 _, [%0];" ::"r"(peer_empty) : "memory");
              }
            }
          }
#pragma unroll
          for (int u = 0; u < 7; u++) {
            a[0] += bf_lo(c[u].x); a[1] += bf_hi(c[u].x); a[2] += bf_lo(c[u].y); a[3] += bf_hi(c[u].y);
            a[4] += bf_lo(c[u].z); a[5] += bf_hi(c[u].z); a[6] += bf_lo(c[u].w); a[7] += bf_hi(c[u].w);
          }
        }
#pragma unroll 1
        for (int o = 2; o < 32; o <<= 1)
#pragma unroll
          for (int e = 0; e < 8; e++) a[e] += __shfl_xor_sync(0xffffffffu, a[e], o);
        mbar_wait(sb + BAR_E, 0);
        const uint32_t tag = *reinterpret_cast<volatile uint32_t*>(smem + SM_EPOCH) + 1;
        if (lane < 2 && id < 28) {
          uint2* dst = &g_csum[((id & 1) * 2 + ((id >> 1) & 1)) * kF + jF * 224 + (id >> 2) * 32 + hw * 16 + lane * 8];
#pragma unroll
          for (int e = 0; e < 8; e++) st_relaxed64(dst + e, __float_as_uint(a[e]), tag);
        }
        if (tid == 448) TL(job ? 3 : 4);
      }
    }
  } else if (wgi == 2) {
    asm volatile("setmaxnreg.inc.sync.aligned.u32 144;");
    const int tw = tid - 256, w = tw >> 5, r = lane >> 2, q = lane & 3;
    const int R0 = tF * 16;
    const uint32_t fd = sb + SM_FD;
    const uint32_t fd16 = (fd & 0x3FFFF) >> 4, t16 = ((sb + SM_T16) & 0x3FFFF) >> 4;

    mbar_wait(sb + BAR_R, 0);
    if (tw == 0) TL(56);
    uint32_t epoch;
    {
      uint32_t xr[28];
#pragma unroll
      for (int i = 0; i < 28; i++)
        asm volatile("ld.shared.b32 %0, [%1];" : "=r"(xr[i]) : "r"(fd + w * (4 * kD * 2) + lane * 4 + i * 128) : "memory");
      bar_sync<1, 128>();
      constexpr float kScale = 1.0f / (2048.0f * 448.0f);
      float twc[3][2], tws[3][2];
#pragma unroll
      for (int c = 1; c <= 3; c++)
#pragma unroll
        for (int e = 0; e < 2; e++) {
          unit_root<448>((2 * lane + e) * c, twc[c - 1][e], tws[c - 1][e]);
          twc[c - 1][e] *= kScale;
          tws[c - 1][e] *= -kScale;
        }
      float m1[4], m2[4], piv[4];
#pragma unroll
      for (int rr = 0; rr < 4; rr++) {
        piv[rr] = __shfl_sync(0xffffffffu, bf_lo(xr[7 * rr]), 0);
        m1[rr] = m2[rr] = 0.f;
#pragma unroll
        for (int a = 0; a < 7; a++) {
          const float d0 = bf_lo(xr[7 * rr + a]) - piv[rr], d1 = bf_hi(xr[7 * rr + a]) - piv[rr];
          m1[rr] += d0 + d1;
          m2[rr] += d0 * d0 + d1 * d1;
        }
      }
#pragma unroll 1
      for (int o = 16; o > 0; o >>= 1)
#pragma unroll
        for (int rr = 0; rr < 4; rr++) {
          m1[rr] += __shfl_xor_sync(0xffffffffu, m1[rr], o);
          m2[rr] += __shfl_xor_sync(0xffffffffu, m2[rr], o);
        }
      uint32_t mb2_l;
      float rden_l;
      {
        const float s1 = (q & 2 ? (q & 1 ? m1[3] : m1[2]) : (q & 1 ? m1[1] : m1[0])) * (1.0f / 448.0f);
        const float s2 = (q & 2 ? (q & 1 ? m2[3] : m2[2]) : (q & 1 ? m2[1] : m2[0])) * (1.0f / 448.0f);
        const float pv = q & 2 ? (q & 1 ? piv[3] : piv[2]) : (q & 1 ? piv[1] : piv[0]);
        mb2_l = pack_bf16(pv + s1, pv + s1);
        const float vb = bf_round(fmaxf(s2 - s1 * s1, 0.f));
        rden_l = 1.0f / bf_round(sqrtf(bf_round(vb + 1e-5f)));
      }
      mbar_wait(sb + BAR_E, 0);
      epoch = *reinterpret_cast<volatile uint32_t*>(smem + SM_EPOCH);
      if (lane < 4) st_relaxed64(&g_stats[R0 + 4 * w + lane], (mb2_l & 0xffff0000u) | ((epoch + 1) & 0xffffu), __float_as_uint(rden_l));
      if (tw == 0) TL(58);
      const uint32_t uchunk = ((lane >> 3) << 1) | (lane & 1);
      const uint32_t ubase = fd + ((lane >> 1) & 3) * 4 + w * 4096;
#pragma unroll 1
      for (int rr = 0; rr < 4; rr++) {
        const uint32_t mb2 = __shfl_sync(0xffffffffu, mb2_l, rr);
        const float rden = __shfl_sync(0xffffffffu, rden_l, rr);
        uint32_t xn2[7];
#pragma unroll
        for (int a = 0; a < 7; a++) {
          const uint32_t d = hsub_bf16x2(xr[a], mb2);
          xn2[a] = pack_bf16(bf_lo(d) * rden, bf_hi(d) * rden);
        }
        float ur[4][2], ui[4][2];
#pragma unroll
        for (int e = 0; e < 2; e++) {
          float xn[7];
#pragma unroll
          for (int a = 0; a < 7; a++) xn[a] = e ? bf_hi(xn2[a]) : bf_lo(xn2[a]);
          const float s1 = xn[1] + xn[6], s2 = xn[2] + xn[5], s3 = xn[3] + xn[4];
          const float d1 = xn[1] - xn[6], d2 = xn[2] - xn[5], d3 = xn[3] - xn[4];
          ur[0][e] = (xn[0] + s1 + s2 + s3) * kScale;
          ui[0][e] = 0.f;
          const float r1 = xn[0] + C1 * s1 + C2 * s2 + C3 * s3, i1 = -(S1 * d1 + S2 * d2 + S3 * d3);
          const float r2 = xn[0] + C2 * s1 + C3 * s2 + C1 * s3, i2 = -(S2 * d1 - S3 * d2 - S1 * d3);
          const float r3 = xn[0] + C3 * s1 + C1 * s2 + C2 * s3, i3 = -(S3 * d1 - S1 * d2 + S2 * d3);
          ur[1][e] = r1 * twc[0][e] - i1 * tws[0][e]; ui[1][e] = r1 * tws[0][e] + i1 * twc[0][e];
          ur[2][e] = r2 * twc[1][e] - i2 * tws[1][e]; ui[2][e] = r2 * tws[1][e] + i2 * twc[1][e];
          ur[3][e] = r3 * twc[2][e] - i3 * tws[2][e]; ui[3][e] = r3 * tws[2][e] + i3 * twc[2][e];
        }
#pragma unroll
        for (int c = 0; c < 4; c++) {
          sts32(ubase + rr * 1024 + (2 * c) * 128 + ((uchunk ^ (2 * c)) << 4), pack_bf16(ur[c][0], ur[c][1]));
          sts32(ubase + rr * 1024 + (2 * c + 1) * 128 + ((uchunk ^ (2 * c + 1)) << 4), pack_bf16(ui[c][0], ui[c][1]));
        }
#pragma unroll
        for (int i = 0; i < 21; i++) xr[i] = xr[i + 7];
      }
    }
    const uint32_t par = (epoch + 1) & 1;
    fence_async_smem();
    if (tw == 0) TL(16);
    bar_sync<1, 128>();

    mbar_wait(sb + BAR_T, 0);
    if (tw == 0) TL2(3, 28);

    float acc[64];
#pragma unroll 1
    for (int hh = 0; hh < 2; hh++) {
      wgmma_fence();
#pragma unroll
      for (int kk = 0; kk < 4; kk++)
        wgmma_ss_n128_tb0(acc, desc_at(t16 + hh * 512, kk * 32, 16, 1024, 1), desc_at(fd16, kk * 32, 16, 1024, 1), kk);
      wgmma_commit();
      wgmma_wait<0>();
      reg_fence(acc);
      if (tw == 0) TL2(3, 29 + hh);
      const int k = q + 7 * (2 * (8 * w + r) + hh);
      const bool cj = k > 224;
      const int col = cj ? 448 - k : k;
      if (!(q == 0 && cj)) {
        const uint32_t sgn = cj ? 0x80008000u : 0u;
        uint32_t re[8], im[8];
#pragma unroll
        for (int pp = 0; pp < 8; pp++) {
          const int j0 = 4 * (pp & 3) + 2 * (pp >> 2), j1 = j0 + 1;
          re[pp] = pack_bf16(acc[4 * j0] - acc[4 * j0 + 3], acc[4 * j1] - acc[4 * j1 + 3]);
          im[pp] = pack_bf16(acc[4 * j0 + 1] + acc[4 * j0 + 2], acc[4 * j1 + 1] + acc[4 * j1 + 2]) ^ sgn;
        }
        uint16_t* dst = &g_At[(size_t)col * 2 * kS + R0];
        stg128(dst, make_uint4(tag_word(re[0], par), re[1], re[2], re[3]));
        stg128(dst + 8, make_uint4(tag_word(re[4], par), re[5], re[6], re[7]));
        stg128(dst + kS, make_uint4(tag_word(im[0], par), im[1], im[2], im[3]));
        stg128(dst + kS + 8, make_uint4(tag_word(im[4], par), im[5], im[6], im[7]));
      }
    }
    bar_sync<1, 128>();
    if (tw == 0) { red_add(&g_cnt[CNT_A], 1); TL(18); }
    mbar_wait(sb + BAR_WT, 0);
    if (tw == 0) TL2(3, 12);
    {
      const uint32_t tile = sb + SM_RING + (10 % kStages) * 16384 + 2 * ((tF >> 2) & 7) + q * (4 * 464) + 2 * (tw >> 2);
      uint32_t* wdst = &g_Wt[(tw >> 2) * kS + (tF >> 2) * 64 + 16 * (tF & 3) + 4 * q];
#pragma unroll 1
      for (int it = 0; it < 2; it++) {
        uint32_t v[4][4];
#pragma unroll
        for (int u = 0; u < 4; u++)
#pragma unroll
          for (int i = 0; i < 4; i++) {
            uint16_t re, im;
            asm volatile("ld.shared.b16 %0, [%1];" : "=h"(re) : "r"(tile + (it * 4 + u) * 64 + i * 464));
            asm volatile("ld.shared.b16 %0, [%1];" : "=h"(im) : "r"(tile + (it * 4 + u) * 64 + (16 + i) * 464));
            v[u][i] = re | ((uint32_t)im << 16);
          }
#pragma unroll
        for (int u = 0; u < 4; u++)
          if ((tw >> 2) + (it * 4 + u) * 32 < kCols)
            stg128(wdst + (it * 4 + u) * 32 * kS, make_uint4(tag_word(v[u][0], par), v[u][1], v[u][2], v[u][3]));
      }
    }
    bar_sync<1, 128>();
    if (tw == 0) {
      uint32_t peer_empty;
      asm("mapa.shared::cluster.u32 %0, %1, %2;" : "=r"(peer_empty) : "r"(sb + BAR_EMPTY + (10 % kStages) * 8), "r"(rank ^ 1));
      mbar_arrive(sb + BAR_EMPTY + (10 % kStages) * 8);
      mbar_arrive(sb + BAR_EMPTY + (10 % kStages) * 8);
      asm volatile("mbarrier.arrive.shared::cluster.b64 _, [%0];" ::"r"(peer_empty) : "memory");
      asm volatile("mbarrier.arrive.shared::cluster.b64 _, [%0];" ::"r"(peer_empty) : "memory");
      TL(14);
    }
    const int c1 = 8 * w + r;
    float tc[16], ts[16];
#pragma unroll
    for (int i = 0; i < 16; i++) unit_root<2048>((16 * (i >> 2) + 4 * q + (i & 3)) * c1, tc[i], ts[i]);
    if (tw == 0) {
      poll_counter(&g_cnt[CNT_A], (epoch + 1) * 128u);
      TL(19);
    }
    bar_sync<1, 128>();

    const int ncol = (tF + 128 < kCols) ? 2 : 1;
    {
      const uint16_t* src = &g_At[(size_t)tF * 2 * kS + 8 * tw];
      const size_t cstep = ncol == 2 ? (size_t)128 * 2 * kS : 0;
      uint4 v[8];
      poll_vecs(v, par, [&](int m) { return src + (m >> 2) * cstep + 1024 * (m & 3); });
      const int pa = phi_inv(tw >> 3);
#pragma unroll
      for (int m = 0; m < 8; m++)
        sts128(fd + (m >> 2) * 8192 + ((m >> 1) & 1) * 4096 + ((m & 1) * 16 + pa) * 128 + (((tw & 7) ^ (pa & 7)) << 4), v[m]);
    }
    if (tw == 0) TL(20);
    fence_async_smem();
    bar_sync<1, 128>();
    if (tw == 0) TL(21);
#pragma unroll 1
    for (int cc = 0; cc < ncol; cc++) {
      const int col = tF + cc * 128;
      const uint32_t xt16 = fd16 + cc * 512;
      uint4 wf[4];
      const uint32_t* wsrc = &g_Wt[(size_t)col * kS + c1 * 64 + 4 * q];
#pragma unroll
      for (int g = 0; g < 4; g++) wf[g] = ld_relaxed128(wsrc + 16 * g);
      wgmma_fence();
#pragma unroll
      for (int kk = 0; kk < 2; kk++)
        wgmma_ss_n128_tb1(acc, desc_at(t16, kk * 32, 16, 1024, 1), desc_at(xt16, kk * 2048, 4096, 1024, 1), kk);
      wgmma_commit();
      wgmma_wait<0>();
      reg_fence(acc);
      uint32_t fa[16];
#pragma unroll
      for (int j = 0; j < 8; j++) {
        float re[2], im[2];
#pragma unroll
        for (int e = 0; e < 2; e++) {
          const float dr = acc[4 * j + e] - acc[4 * (j + 8) + 2 + e];
          const float di = acc[4 * (j + 8) + e] + acc[4 * j + 2 + e];
          const int i = 2 * j + e;
          re[e] = dr * tc[i] + di * ts[i];
          im[e] = di * tc[i] - dr * ts[i];
        }
        fa[2 * j + 0] = pack_bf16(re[0], re[1]);
        fa[2 * j + 1] = pack_bf16(im[0], im[1]);
      }
      wgmma_fence();
#pragma unroll
      for (int kk = 0; kk < 4; kk++)
        wgmma_rs_n128_tb0(acc, fa[4 * kk], fa[4 * kk + 1], fa[4 * kk + 2], fa[4 * kk + 3], desc_at(t16, kk * 32, 16, 1024, 1), kk);
      wgmma_commit();
      wgmma_wait<0>();
      reg_fence(acc);
#pragma unroll
      for (int g = 0; g < 4; g++)
        if ((wf[g].x ^ par) & 1) wf[g] = poll_vec(wsrc + 16 * g, par);
#pragma unroll
      for (int g = 0; g < 4; g++) {
        const uint32_t wv[4] = {wf[g].x, wf[g].y, wf[g].z, wf[g].w};
#pragma unroll
        for (int e = 0; e < 2; e++) {
          float yr[2], yi[2];
#pragma unroll
          for (int o = 0; o < 2; o++) {
            const int G = 4 * o + g;
            const float re = acc[8 * G + e] - acc[8 * G + 6 + e];
            const float im = acc[8 * G + 4 + e] + acc[8 * G + 2 + e];
            const float fr = bf_lo(wv[2 * e + o]), fi = bf_hi(wv[2 * e + o]);
            yr[o] = re * fr - im * fi;
            yi[o] = re * fi + im * fr;
          }
          fa[4 * g + 2 * e + 0] = pack_bf16(yr[0], yr[1]);
          fa[4 * g + 2 * e + 1] = pack_bf16(yi[0], yi[1]);
        }
      }
      wgmma_fence();
#pragma unroll
      for (int kk = 0; kk < 4; kk++)
        wgmma_rs_n128_tb0(acc, fa[4 * kk], fa[4 * kk + 1], fa[4 * kk + 2], fa[4 * kk + 3], desc_at(t16, kk * 32, 16, 1024, 1), kk);
      wgmma_commit();
      wgmma_wait<0>();
      reg_fence(acc);
      bar_sync<1, 128>();
      {
        const int pc = phi_inv(c1);
        const uint32_t xt = fd + cc * 8192 + pc * 128;
#pragma unroll
        for (int e = 0; e < 2; e++) {
          uint32_t tr[4], ti[4];
#pragma unroll
          for (int g = 0; g < 4; g++) {
            float re[2], im[2];
#pragma unroll
            for (int o = 0; o < 2; o++) {
              const int G = 4 * o + g, i = 4 * g + 2 * e + o;
              const float a_ = acc[8 * G + e] + acc[8 * G + 6 + e];
              const float b_ = acc[8 * G + 2 + e] - acc[8 * G + 4 + e];
              re[o] = a_ * tc[i] - b_ * ts[i];
              im[o] = a_ * ts[i] + b_ * tc[i];
            }
            tr[g] = pack_bf16(re[0], re[1]);
            ti[g] = pack_bf16(im[0], im[1]);
          }
          const uint32_t off = ((2 * q + e) ^ (pc & 7)) << 4;
          sts128(xt + off, make_uint4(tr[0], tr[1], tr[2], tr[3]));
          sts128(xt + 4096 + off, make_uint4(ti[0], ti[1], ti[2], ti[3]));
        }
      }
      fence_async_smem();
      bar_sync<1, 128>();
      wgmma_fence();
#pragma unroll
      for (int kk = 0; kk < 2; kk++)
        wgmma_ss_n128_tb1(acc, desc_at(t16, kk * 32, 16, 1024, 1), desc_at(xt16, kk * 2048, 4096, 1024, 1), kk);
      wgmma_commit();
      wgmma_wait<0>();
      reg_fence(acc);
      {
        uint32_t re[8], im[8];
#pragma unroll
        for (int j = 0; j < 8; j++) {
          re[j] = pack_bf16(acc[4 * j] + acc[4 * (j + 8) + 2], acc[4 * j + 1] + acc[4 * (j + 8) + 3]);
          im[j] = pack_bf16(acc[4 * (j + 8)] - acc[4 * j + 2], acc[4 * (j + 8) + 1] - acc[4 * j + 3]);
        }
        uint16_t* dst = &g_Zt[(size_t)col * 2 * kS + 64 * c1 + 16 * q];
        stg128(dst, make_uint4(tag_word(re[0], par), re[1], re[2], re[3]));
        stg128(dst + 8, make_uint4(tag_word(re[4], par), re[5], re[6], re[7]));
        stg128(dst + kS, make_uint4(tag_word(im[0], par), im[1], im[2], im[3]));
        stg128(dst + kS + 8, make_uint4(tag_word(im[4], par), im[5], im[6], im[7]));
      }
      if (tw == 0) TL2(3, cc);
    }
    bar_sync<1, 128>();
    if (tw == 0) {
      red_add(&g_cnt[CNT_Z], 1);
      TL(22);
      poll_counter(&g_cnt[CNT_Z], (epoch + 1) * 128u);
    }
    bar_sync<1, 128>();

    {
      const int c = (tw >> 2) & 3, ri = (tw >> 1) & 1;
      const uint32_t dst = fd + ((tw >> 3) & 1) * 8192 + (tw >> 4) * 128 + (((tw & 7) ^ ((tw >> 4) & 7)) << 4);
      uint4 v[8];
      const uint16_t* zsrc = &g_Zt[(size_t)ri * kS + R0 + 8 * (tw & 1)];
      poll_vecs(v, par, [&](int m) {
        const int k = c + 7 * phi(8 * m + (tw >> 4));
        return zsrc + (size_t)(k > 224 ? 448 - k : k) * 2 * kS;
      });
#pragma unroll
      for (int m = 0; m < 8; m++) {
        const uint32_t sg = (ri && c + 7 * phi(8 * m + (tw >> 4)) > 224) ? 0x80008000u : 0u;
        sts128(dst + m * 1024, make_uint4(v[m].x ^ sg, v[m].y ^ sg, v[m].z ^ sg, v[m].w ^ sg));
      }
    }
    fence_async_smem();
    bar_sync<1, 128>();
    if (blockIdx.x == 0 && tw == 0) *(volatile uint32_t*)&g_cnt[0] = epoch + 1;
    if (tw == 0) TL(23);
    {
      uint32_t y16[2][14];
#pragma unroll 1
      for (int hh = 0; hh < 2; hh++) {
        wgmma_fence();
#pragma unroll
        for (int kk = 0; kk < 4; kk++)
          wgmma_ss_n128_tb1(acc, desc_at(t16 + hh * 512, kk * 32, 16, 1024, 1), desc_at(fd16, kk * 2048, 8192, 1024, 1), kk);
        wgmma_commit();
        wgmma_wait<0>();
        reg_fence(acc);
        const int b = 2 * (8 * w + r) + hh;
        float uc[3], us[3];
#pragma unroll
        for (int c = 1; c <= 3; c++) {
          unit_root<448>(b * c, uc[c - 1], us[c - 1]);
          uc[c - 1] *= 2.f;
          us[c - 1] *= 2.f;
        }
#pragma unroll
        for (int i = 0; i < 14; i++) y16[0][i] = y16[1][i];
#pragma unroll
        for (int jr = 0; jr < 2; jr++) {
          float y[2][7];
#pragma unroll
          for (int e = 0; e < 2; e++) {
            float A[3], B[3];
            const float t0 = acc[4 * jr + e] + acc[4 * (2 + jr) + 2 + e];
#pragma unroll
            for (int c = 1; c <= 3; c++) {
              const float tr = acc[4 * (4 * c + jr) + e] + acc[4 * (4 * c + 2 + jr) + 2 + e];
              const float ti = acc[4 * (4 * c + 2 + jr) + e] - acc[4 * (4 * c + jr) + 2 + e];
              A[c - 1] = tr * uc[c - 1] - ti * us[c - 1];
              B[c - 1] = tr * us[c - 1] + ti * uc[c - 1];
            }
            const float p1 = t0 + C1 * A[0] + C2 * A[1] + C3 * A[2], q1 = S1 * B[0] + S2 * B[1] + S3 * B[2];
            const float p2 = t0 + C2 * A[0] + C3 * A[1] + C1 * A[2], q2 = S2 * B[0] - S3 * B[1] - S1 * B[2];
            const float p3 = t0 + C3 * A[0] + C1 * A[1] + C2 * A[2], q3 = S3 * B[0] - S1 * B[1] + S2 * B[2];
            y[e][0] = t0 + A[0] + A[1] + A[2];
            y[e][1] = p1 - q1; y[e][6] = p1 + q1;
            y[e][2] = p2 - q2; y[e][5] = p2 + q2;
            y[e][3] = p3 - q3; y[e][4] = p3 + q3;
          }
#pragma unroll
          for (int a = 0; a < 7; a++) y16[1][7 * jr + a] = pack_bf16(y[0][a], y[1][a]);
        }
      }
      bar_sync<1, 128>();
      const uint32_t sdst = fd + w * 512 + (r & 3) * 16 + (r >> 2) * 8 + q * 128;
#pragma unroll
      for (int jr = 0; jr < 2; jr++)
#pragma unroll
        for (int a = 0; a < 7; a++) {
          const uint32_t lo = y16[0][7 * jr + a], hi = y16[1][7 * jr + a];
          sts32(sdst + a * 2048 + jr * 4, __byte_perm(lo, hi, 0x5410));
          sts32(sdst + a * 2048 + jr * 4 + 64, __byte_perm(lo, hi, 0x7632));
        }
    }
    bar_sync<1, 128>();
    if (tw == 0) TL(24);

    const uint4* pbase = &g_P[(size_t)tF * 8 * 896 + tw];
    __nv_bfloat16* obase = p.out + (size_t)(R0 + r) * kD + 16 * w + 2 * q;
    const __nv_bfloat16* xbase = p.x + (size_t)(R0 + r) * kD + 16 * w + 2 * q;
    uint4 nx[8];
    uint32_t xn[4];
#pragma unroll
    for (int s = 0; s < 8; s++) nx[s] = ld_relaxed128(pbase + s * 896);
#pragma unroll
    for (int g = 0; g < 4; g++) xn[g] = __ldg(reinterpret_cast<const uint32_t*>(xbase + (g & 1) * 8 * kD + (g >> 1) * 8));
#pragma unroll 1
    for (int ps = 0; ps < 7; ps++) {
      uint4 pv[8];
      uint32_t bad = 0;
#pragma unroll
      for (int s = 0; s < 8; s++) {
        pv[s] = nx[s];
        bad |= pv[s].x ^ par;
      }
      if (__any_sync(0xffffffffu, bad & 1)) {
        if (lane == 0) poll_counter(&g_cnt[CNT_P + tF * 8 + ps], (epoch + 1) * 8u);
        __syncwarp();
        poll_vecs(pv, par, [&](int s) { return pbase + s * 896 + ps * 128; });
      }
      uint32_t xv[4];
#pragma unroll
      for (int g = 0; g < 4; g++) xv[g] = xn[g];
      if (ps < 6) {
#pragma unroll
        for (int s = 0; s < 8; s++) nx[s] = ld_relaxed128(pbase + s * 896 + (ps + 1) * 128);
#pragma unroll
        for (int g = 0; g < 4; g++)
          xn[g] = __ldg(reinterpret_cast<const uint32_t*>(xbase + (g & 1) * 8 * kD + 64 * (ps + 1) + (g >> 1) * 8));
      }
      if (tw == 0) TL(25 + ps);
      const uint4 sv = lds128(fd + ps * 2048 + tw * 16);
      float sum[8];
#pragma unroll
      for (int e = 0; e < 8; e++) sum[e] = 0.f;
#pragma unroll
      for (int s = 0; s < 8; s++) {
        sum[0] += bf_lo(pv[s].x); sum[1] += bf_hi(pv[s].x); sum[2] += bf_lo(pv[s].y); sum[3] += bf_hi(pv[s].y);
        sum[4] += bf_lo(pv[s].z); sum[5] += bf_hi(pv[s].z); sum[6] += bf_lo(pv[s].w); sum[7] += bf_hi(pv[s].w);
      }
      const uint32_t sreg[4] = {sv.x, sv.y, sv.z, sv.w};
#pragma unroll
      for (int g = 0; g < 4; g++) {
        const uint32_t dd = pack_bf16(sum[2 * g], sum[2 * g + 1]);
        const uint32_t gg = pack_bf16(silu_f(bf_lo(dd)), silu_f(bf_hi(dd)));
        *reinterpret_cast<uint32_t*>(obase + (g & 1) * 8 * kD + 64 * ps + (g >> 1) * 8) = hadd_bf16x2(xv[g], hmul_bf16x2(sreg[g], gg));
      }
    }
    if (tw == 0) { TL(32); TLG(62); }
  } else {
    asm volatile("setmaxnreg.inc.sync.aligned.u32 160;");
    const int g = warp >> 2, w = warp & 3, r = lane >> 2, q = lane & 3;
    const bool elected = (tid & 127) == 0;
    const uint32_t gu = __shfl_sync(0xffffffffu, (uint32_t)g, 0);
    const uint32_t xa16 = (((sb + SM_X) & 0x3FFFF) + gu * 8192) >> 4, ring16 = ((sb + SM_RING) & 0x3FFFF) >> 4;
    uint32_t peer_empty;
    asm("mapa.shared::cluster.u32 %0, %1, %2;" : "=r"(peer_empty) : "r"(sb + BAR_EMPTY), "r"(rank ^ 1));
    uint32_t h[56];
    RowStat st0, st1;
    Ring rg;
    uint32_t prev = 0;
    auto release_prev = [&]() {
      if (elected) {
        mbar_arrive(sb + BAR_EMPTY + prev * 8);
        asm volatile("mbarrier.arrive.shared::cluster.b64 _, [%0];" ::"r"(peer_empty + prev * 8) : "memory");
      }
    };
    const uint32_t cs = sb + SM_CS + q * 8;
    {
      float acc[96];
#pragma unroll 1
      for (int ks = 0; ks < 14; ks++) {
        if (gu == 1 && ks == 14 - kLag) bar_sync<3, 256>();
        if (ks == 10) rg.advance();
        if ((ks & 1) == 0) mbar_wait(sb + BAR_X + (ks >> 1) * 8, 0);
        mbar_wait(sb + BAR_FULL + rg.slot * 8, rg.phase);
        TLS(1 + g, ks);
        const uint32_t a16 = xa16 + (ks >> 1) * 1024 + (ks & 1) * 4, b16 = ring16 + rg.slot * 1024;
        wgmma_fence();
        wgmma_ss_n192_tb1(acc, desc_at(a16, 0, 16, 1024, 1), desc_at(b16, 0, 2048, 512, 2), ks);
        wgmma_commit();
        if (ks > 0) { wgmma_wait<1>(); release_prev(); }
        wgmma_ss_n192_tb1(acc, desc_at(a16, 32, 16, 1024, 1), desc_at(b16, 1024, 2048, 512, 2), 1);
        wgmma_commit();
        prev = rg.slot;
        rg.advance();
      }
      wgmma_wait<0>();
      reg_fence(acc);
      release_prev();
      if (gu == 0) asm volatile("bar.arrive 3, 256;" ::: "memory");
      if (elected) TL(36 + g * 12);
      mbar_wait(sb + BAR_S, 0);
      {
        const float2 s0 = lds64f(sb + SM_STATS + (g * 64 + w * 16 + r) * 8);
        const float2 s1 = lds64f(sb + SM_STATS + (g * 64 + w * 16 + r + 8) * 8);
        st0 = RowStat{s0.x, 0.5f * s0.y, 0.5f * s0.y * s0.y};
        st1 = RowStat{s1.x, 0.5f * s1.y, 0.5f * s1.y * s1.y};
      }
      swiglu_atom<0, 48, 32>(acc, h, cs, st0, st1);
      swiglu_atom<16, 64, 40>(acc, h, cs + 128, st0, st1);
      swiglu_atom<32, 80, 48>(acc, h, cs + 256, st0, st1);
      if (elected) TL(37 + g * 12);
    }
    float acc[64];
#pragma unroll 1
    for (int ps = 0; ps < 2; ps++) {
#pragma unroll 1
      for (int ks = 0; ks < 7; ks++) {
        if (gu == 1 && ks == 7 - kLag) bar_sync<3, 256>();
        if (ps == 0 && ks == 1) rg.advance();
        mbar_wait(sb + BAR_FULL + rg.slot * 8, rg.phase);
        TLS(1 + g, 14 + ps * 7 + ks);
        const uint32_t a16 = xa16 + ks * 1024, b16 = ring16 + rg.slot * 1024;
        wgmma_fence();
        wgmma_ss_n128_tb1(acc, desc_at(a16, 0, 16, 1024, 1), desc_at(b16, 0, 4096, 512, 2), ks);
        wgmma_commit();
        if (ks > 0) { wgmma_wait<1>(); release_prev(); }
#pragma unroll
        for (int k = 1; k < 4; k++)
          wgmma_ss_n128_tb1(acc, desc_at(a16, k * 32, 16, 1024, 1), desc_at(b16, k * 1024, 4096, 512, 2), 1);
        wgmma_commit();
        prev = rg.slot;
        rg.advance();
      }
      wgmma_wait<0>();
      reg_fence(acc);
      release_prev();
      if (gu == 0) asm volatile("bar.arrive 3, 256;" ::: "memory");
      if (ps == 1 && elected) {
        uint32_t peer_xf;
        asm("mapa.shared::cluster.u32 %0, %1, %2;" : "=r"(peer_xf) : "r"(sb + BAR_XF), "r"(rank ^ 1));
        mbar_arrive(sb + BAR_XF);
        asm volatile("mbarrier.arrive.shared::cluster.b64 _, [%0];" ::"r"(peer_xf) : "memory");
      }
      if (elected) TL(38 + 2 * ps + g * 12);
      mbar_wait(sb + BAR_S1 + ps * 8, 0);
#pragma unroll
      for (int i = 0; i < 40; i++) h[i] = h[i + 16];
      swiglu_atom<0, 32, 40>(acc, h, cs + (96 + 64 * ps) * 4, st0, st1);
      swiglu_atom<16, 48, 48>(acc, h, cs + (128 + 64 * ps) * 4, st0, st1);
      if (elected) TL(39 + 2 * ps + g * 12);
    }
    mbar_wait(sb + BAR_E, 0);
    const uint32_t par = (*reinterpret_cast<volatile uint32_t*>(smem + SM_EPOCH) + 1) & 1;
    uint4* pdst = &g_P[((size_t)(iB * 8 + g * 4 + w) * 8 + jF) * 896 + lane];
    uint32_t* hint = &g_cnt[CNT_P + (iB * 8 + g * 4 + w) * 8];
    const uint32_t one = lane == 0;
    float dA[32], dB[32];
    const uint32_t xb16 = ((sb + SM_X) & 0x3FFFF) >> 4;
    auto stage = [&](float(&d)[32], int ld, bool second) {
      uint32_t b16;
      if (ld >= 5 && ld < 12) {
        mbar_wait(sb + BAR_X + (ld - 5) * 8, 1);
        b16 = xb16 + (ld - 5) * 1024;
      } else {
        mbar_wait(sb + BAR_FULL + rg.slot * 8, rg.phase);
        b16 = ring16 + rg.slot * 1024;
        prev = rg.slot;
        rg.advance();
      }
      TLS(1 + g, 28 + ld);
      wgmma_fence();
      if (!second) {
#pragma unroll
        for (int k = 0; k < 8; k++)
          wgmma_rs_n64_tb1(d, h[4 * k], h[4 * k + 1], h[4 * k + 2], h[4 * k + 3], desc_at(b16, k * 2048, 8192, 1024, 1), k);
      } else {
#pragma unroll
        for (int k = 0; k < 6; k++)
          wgmma_rs_n64_tb1(d, h[32 + 4 * k], h[33 + 4 * k], h[34 + 4 * k], h[35 + 4 * k], desc_at(b16, k * 2048, 8192, 1024, 1), 1);
      }
      wgmma_commit();
    };
    auto write_out = [&](float(&d)[32], int ps) {
      reg_fence(d);
      uint4* dst = pdst + ps * 128;
#pragma unroll
      for (int v = 0; v < 4; v++)
        stg128(dst + v * 32, make_uint4(tag_word(pack_bf16(d[8 * v], d[8 * v + 1]), par), pack_bf16(d[8 * v + 2], d[8 * v + 3]),
                                        pack_bf16(d[8 * v + 4], d[8 * v + 5]), pack_bf16(d[8 * v + 6], d[8 * v + 7])));
      if (one) red_add(hint + ps, one);
      if (elected) TL2(6 + g, ps);
    };
    auto release_slot01 = [&](int slot) {
      if (elected) {
        mbar_arrive(sb + BAR_EMPTY + slot * 8);
        asm volatile("mbarrier.arrive.shared::cluster.b64 _, [%0];" ::"r"(peer_empty + slot * 8) : "memory");
      }
    };
    const uint32_t slot0 = rg.slot;
    stage(dA, 0, false);
#pragma unroll 1
    for (int ps = 0; ps < 7; ps += 2) {
      stage(dA, 2 * ps + 1, true);
      wgmma_wait<1>();
      if (ps == 0) release_slot01(slot0);
      if (ps + 1 < 7) {
        stage(dB, 2 * ps + 2, false);
        wgmma_wait<1>();
        if (ps == 0) release_slot01(slot0 == kStages - 1 ? 0 : slot0 + 1);
        write_out(dA, ps);
        stage(dB, 2 * ps + 3, true);
        wgmma_wait<1>();
        stage(dA, 2 * ps + 4, false);
        wgmma_wait<1>();
        write_out(dB, ps + 1);
      } else {
        wgmma_wait<0>();
        write_out(dA, ps);
      }
    }
  }
}

typedef CUresult (*EncodeTiledFn)(CUtensorMap*, CUtensorMapDataType, cuuint32_t, void*, const cuuint64_t*, const cuuint64_t*,
                                  const cuuint32_t*, const cuuint32_t*, CUtensorMapInterleave, CUtensorMapSwizzle,
                                  CUtensorMapL2promotion, CUtensorMapFloatOOBfill);

}

extern "C" void kernel_launch(void* const* d_in, const int* in_sizes, int n_in, void* d_out, int out_size) {
  (void)in_sizes; (void)n_in; (void)out_size;
  static EncodeTiledFn enc = nullptr;
  if (!enc) {
    void* fn = nullptr;
    cudaDriverEntryPointQueryResult st;
    cudaGetDriverEntryPoint("cuTensorMapEncodeTiled", &fn, cudaEnableDefault, &st);
    enc = (EncodeTiledFn)fn;
    cudaFuncSetAttribute(fused_gfnet_ffn_kernel, cudaFuncAttributeMaxDynamicSharedMemorySize, SM_TOTAL);
  }
  CUtensorMap tmX, tmG3, tmU3, tmG2, tmU2, tmD, tmWR, tmWI, tmCG, tmCU;
  const cuuint32_t es[3] = {1, 1, 1};
  {
    const cuuint64_t gd[2] = {kD, kS}, gs[1] = {kD * 2};
    const cuuint32_t bx[2] = {64, 128};
    enc(&tmX, CU_TENSOR_MAP_DATA_TYPE_BFLOAT16, 2, d_in[0], gd, gs, bx, es, CU_TENSOR_MAP_INTERLEAVE_NONE,
        CU_TENSOR_MAP_SWIZZLE_128B, CU_TENSOR_MAP_L2_PROMOTION_L2_128B, CU_TENSOR_MAP_FLOAT_OOB_FILL_NONE);
  }
  {
    const cuuint64_t gd[3] = {32, kD, kF / 32}, gs[2] = {kF * 2, 64};
    const cuuint32_t b3[3] = {32, 32, 3}, b2[3] = {32, 64, 2};
    CUtensorMap* maps[4] = {&tmG3, &tmU3, &tmG2, &tmU2};
    for (int i = 0; i < 4; i++)
      enc(maps[i], CU_TENSOR_MAP_DATA_TYPE_BFLOAT16, 3, d_in[4 + (i & 1)], gd, gs, i < 2 ? b3 : b2, es,
          CU_TENSOR_MAP_INTERLEAVE_NONE, CU_TENSOR_MAP_SWIZZLE_64B, CU_TENSOR_MAP_L2_PROMOTION_L2_128B,
          CU_TENSOR_MAP_FLOAT_OOB_FILL_NONE);
  }
  {
    const cuuint64_t gd[2] = {kD, kF}, gs[1] = {kD * 2};
    const cuuint32_t bx[2] = {64, 32};
    enc(&tmD, CU_TENSOR_MAP_DATA_TYPE_BFLOAT16, 2, d_in[6], gd, gs, bx, es, CU_TENSOR_MAP_INTERLEAVE_NONE,
        CU_TENSOR_MAP_SWIZZLE_128B, CU_TENSOR_MAP_L2_PROMOTION_L2_128B, CU_TENSOR_MAP_FLOAT_OOB_FILL_NONE);
  }
  {
    const cuuint64_t gd[2] = {kF, kD}, gs[1] = {kF * 2};
    const cuuint32_t bx[2] = {32, 224};
    enc(&tmCG, CU_TENSOR_MAP_DATA_TYPE_BFLOAT16, 2, d_in[4], gd, gs, bx, es, CU_TENSOR_MAP_INTERLEAVE_NONE,
        CU_TENSOR_MAP_SWIZZLE_NONE, CU_TENSOR_MAP_L2_PROMOTION_L2_128B, CU_TENSOR_MAP_FLOAT_OOB_FILL_NONE);
    enc(&tmCU, CU_TENSOR_MAP_DATA_TYPE_BFLOAT16, 2, d_in[5], gd, gs, bx, es, CU_TENSOR_MAP_INTERLEAVE_NONE,
        CU_TENSOR_MAP_SWIZZLE_NONE, CU_TENSOR_MAP_L2_PROMOTION_L2_128B, CU_TENSOR_MAP_FLOAT_OOB_FILL_NONE);
  }
  {
    const cuuint64_t gd[2] = {32 * kCols, 64}, gs[1] = {32 * kCols * 2};
    const cuuint32_t bx[2] = {232, 16};
    enc(&tmWR, CU_TENSOR_MAP_DATA_TYPE_BFLOAT16, 2, d_in[1], gd, gs, bx, es, CU_TENSOR_MAP_INTERLEAVE_NONE,
        CU_TENSOR_MAP_SWIZZLE_NONE, CU_TENSOR_MAP_L2_PROMOTION_L2_128B, CU_TENSOR_MAP_FLOAT_OOB_FILL_NONE);
    enc(&tmWI, CU_TENSOR_MAP_DATA_TYPE_BFLOAT16, 2, d_in[2], gd, gs, bx, es, CU_TENSOR_MAP_INTERLEAVE_NONE,
        CU_TENSOR_MAP_SWIZZLE_NONE, CU_TENSOR_MAP_L2_PROMOTION_L2_128B, CU_TENSOR_MAP_FLOAT_OOB_FILL_NONE);
  }
  Params prm;
  prm.x = (const __nv_bfloat16*)d_in[0];
  prm.wr = (const uint16_t*)d_in[1];
  prm.wi = (const uint16_t*)d_in[2];
  prm.wg = (const __nv_bfloat16*)d_in[4];
  prm.wu = (const __nv_bfloat16*)d_in[5];
  prm.wd = (const __nv_bfloat16*)d_in[6];
  prm.out = (__nv_bfloat16*)d_out;
  fused_gfnet_ffn_kernel<<<128, 512, SM_TOTAL>>>(tmX, tmG3, tmU3, tmG2, tmU2, tmD, tmWR, tmWI, tmCG, tmCU, prm);
}
```
